```python
import torch

def _softmax(x, axis=-1):
    return torch.softmax(x, dim=axis)
def _gelu(x):
    return torch.nn.functional.gelu(x, approximate="tanh")
def _silu(x):
    return torch.nn.functional.silu(x)
def _sigmoid(x):
    return torch.sigmoid(x)
def _layernorm(x, axis=-1, eps=1e-5):
    m = x.mean(dim=axis, keepdim=True)
    v = x.var(dim=axis, keepdim=True, unbiased=False)
    return (x - m) / torch.sqrt(v + eps)
def _scatter_add(tgt, idx, src, axis=0):
    return tgt.clone().index_add_(axis, idx, src)
def _segment_sum(src, seg, n):
    out = torch.zeros((n,) + src.shape[1:], dtype=src.dtype)
    return out.index_add_(0, seg, src)
def _pad(x, pw):
    flat = tuple(v for pair in reversed(pw) for v in pair)
    return torch.nn.functional.pad(x, flat)

kernel_name = 'parallel_sum__sliding_local_dilated__glu_gated_swiglu__prompt'

def setup_inputs():

    _w = (lambda a: (lambda t: t.to(torch.bfloat16) if t.is_floating_point() else t)(torch.as_tensor(a)))
    def _A_setup():
        B, S, D = 1, 2048, 640
        return {
            "x": _w((lambda *s: torch.randn(*s, dtype=torch.bfloat16) * 0.05)(B, S, D)),
            "wqkv": _w((lambda *s: torch.randn(*s, dtype=torch.bfloat16) * 0.05)(D, 3 * D)),
            "wo": _w((lambda *s: torch.randn(*s, dtype=torch.bfloat16) * 0.05)(D, D)),
        }
    _A_in = _A_setup()

    def _B_setup():
        B, S, D, F = 1, 2048, 640, 1536
        return {
            "x": _w((lambda *s: torch.randn(*s, dtype=torch.bfloat16) * 0.05)(B, S, D)),
            "w1": _w((lambda *s: torch.randn(*s, dtype=torch.bfloat16) * 0.8)(D, F) * (2.0 / D) ** 0.5),
            "w3": _w((lambda *s: torch.randn(*s, dtype=torch.bfloat16) * 0.8)(D, F) * (2.0 / D) ** 0.5),
            "w2": _w((lambda *s: torch.randn(*s, dtype=torch.bfloat16) * 0.8)(F, D) * (2.0 / F) ** 0.5),
        }
    _B_in = _B_setup()

    return {
        "A_x": _A_in["x"],
        "A_wqkv": _A_in["wqkv"],
        "A_wo": _A_in["wo"],
        "B_x": _B_in["x"],
        "B_w1": _B_in["w1"],
        "B_w3": _B_in["w3"],
        "B_w2": _B_in["w2"],
    }

def reference(A_x, A_wqkv, A_wo, B_x, B_w1, B_w3, B_w2):
    def _A_ref(x, wqkv, wo):
        B, S, D = x.shape
        H = 32; Dh = D // H
        W, dil = 8, 2
        qkv = (lambda x, *d: x.permute(*d))((x @ wqkv).reshape(B, S, 3, H, Dh), 2, 0, 3, 1, 4)
        q, k, v = qkv[0], qkv[1], qkv[2]
        scale = Dh ** -0.5
        pos = torch.arange(S)
        off = torch.arange(W) * dil
        idx = pos[:, None] - off[None, :]
        mask = idx >= 0
        idx_c = torch.where(mask, idx, 0).reshape(-1)
        kg = k[:, :, idx_c, :].reshape(B, H, S, W, Dh)
        vg = v[:, :, idx_c, :].reshape(B, H, S, W, Dh)
        logits = torch.einsum("bhsd,bhswd->bhsw", q, kg) * scale
        logits = torch.where(mask[None, None, :, :], logits, -1e9)
        attn = _softmax(logits, axis=-1)
        o = torch.einsum("bhsw,bhswd->bhsd", attn, vg)
        return (lambda x, *d: x.permute(*d))(o, 0, 2, 1, 3).reshape(B, S, D) @ wo

    def _B_ref(x, w1, w3, w2):
        gate = torch.einsum("bsd,df->bsf", x, w1)
        up = torch.einsum("bsd,df->bsf", x, w3)
        h = _silu(gate) * up
        out = torch.einsum("bsf,fd->bsd", h, w2)
        return out

    x = A_x
    xn = _layernorm(x, axis=-1)
    return x + _A_ref(xn, A_wqkv, A_wo) + _B_ref(xn, B_w1, B_w3, B_w2)
```

```cpp
#include <cuda_runtime.h>
#include <cuda_bf16.h>
#include <cuda.h>
#include <stdint.h>

namespace {

constexpr int kS = 2048, kD = 640, kF = 1536;
constexpr int kActLd = kD + kF;

constexpr uint32_t SM_X = 0;
constexpr uint32_t SM_RING = 163840;
constexpr uint32_t SM_MISC = 229376;
constexpr uint32_t SM_BAR = SM_MISC;
constexpr uint32_t SM_CS = SM_MISC + 320;
constexpr uint32_t SM_CSACC = SM_CS + 2496;
constexpr uint32_t SM_EPOCH = SM_CSACC + 128;
constexpr uint32_t SM_TOTAL = 232448;
constexpr uint32_t G_STAGE = 40960;

constexpr int B_XFULL = 0;
constexpr int B_RFULL = 10;
constexpr int B_REMPTY = 14;
constexpr int B_GFULL = 18;
constexpr int B_GEMPTY = 23;
constexpr int B_CS = 28;
constexpr int B_HALOW = 29;
constexpr int B_HALOR = 30;
constexpr int B_WDONE = 32;
constexpr int B_PART = 37;
constexpr int B_COUNT = 38;

constexpr int kSetupArrivals = 156;
constexpr int NT_E = 15, NT_L = 19;

__device__ __align__(1024) __nv_bfloat16 g_act[kS * kActLd];
__device__ __align__(128) float g_cs[4992];
__device__ __align__(128) float2 g_stats[kS];
__device__ __align__(128) uint4 g_halo[16 * 8 * 2 * 4 * 5 * 32];
__device__ __align__(128) float4 g_part[16 * 4 * 20 * 256];
__device__ __align__(128) unsigned g_cntA[32];
__device__ __align__(128) unsigned g_cntO[16 * 32];
__device__ __align__(128) unsigned g_cntH[16 * 3 * 32];
__device__ __align__(128) unsigned g_flagHalo[16 * 8 * 32];
__device__ __align__(128) unsigned g_flagPart[16 * 4 * 32];
#define TRACE(slot) do { } while (0)

struct Maps {
    CUtensorMap x, wq, wqr, w1, w3, act, wo2, wo1, w22, w21;
};

__device__ __forceinline__ long long gtime() { long long t; asm volatile("mov.u64 %0, %%globaltimer;" : "=l"(t)); return t; }
__device__ __forceinline__ uint32_t smem_u32(const void* p) { return (uint32_t)__cvta_generic_to_shared(p); }
__device__ __forceinline__ uint32_t launder(uint32_t x) { uint32_t y; asm volatile("mov.u32 %0, %1;" : "=r"(y) : "r"(x)); return y; }
__device__ __forceinline__ bool elect_one() {
    uint32_t p;
    asm volatile("{\n.reg .pred P;\nelect.sync _|P, 0xffffffff;\nselp.u32 %0,1,0,P;\n}" : "=r"(p));
    return p;
}
__device__ __forceinline__ void mbar_init(uint32_t bar, uint32_t cnt) { asm volatile("mbarrier.init.shared::cta.b64 [%0], %1;" ::"r"(bar), "r"(cnt)); }
__device__ __forceinline__ void mbar_expect_tx(uint32_t bar, uint32_t bytes) {
    asm volatile("mbarrier.arrive.expect_tx.shared::cta.b64 _, [%0], %1;" ::"r"(bar), "r"(bytes) : "memory");
}
__device__ __forceinline__ void mbar_arrive(uint32_t bar) { asm volatile("mbarrier.arrive.shared::cta.b64 _, [%0];" ::"r"(bar) : "memory"); }
__device__ __forceinline__ void mbar_arrive_cluster(uint32_t bar_cluster_addr) {
    asm volatile("mbarrier.arrive.shared::cluster.b64 _, [%0];" ::"r"(bar_cluster_addr) : "memory");
}
__device__ __forceinline__ uint32_t mapa(uint32_t addr, uint32_t cta) {
    uint32_t r; asm("mapa.shared::cluster.u32 %0, %1, %2;" : "=r"(r) : "r"(addr), "r"(cta)); return r;
}
__device__ __forceinline__ bool mbar_try(uint32_t bar, uint32_t parity) {
    uint32_t ok;
    asm volatile("{\n.reg .pred p;\nmbarrier.try_wait.parity.shared::cta.b64 p, [%1], %2;\nselp.u32 %0,1,0,p;\n}"
                 : "=r"(ok) : "r"(bar), "r"(parity) : "memory");
    return ok;
}
__device__ __forceinline__ void mbar_wait(uint32_t bar, uint32_t parity) {
    int it = 0;
#pragma unroll 1
    while (!mbar_try(bar, parity)) { if (++it > (1 << 17)) break; }
}
__device__ __forceinline__ void tma2(uint32_t dst, const CUtensorMap* m, int c0, int c1, uint32_t bar) {
    asm volatile("cp.async.bulk.tensor.2d.shared::cluster.global.mbarrier::complete_tx::bytes [%0], [%1, {%3, %4}], [%2];"
                 ::"r"(dst), "l"(m), "r"(bar), "r"(c0), "r"(c1) : "memory");
}
__device__ __forceinline__ void tma3(uint32_t dst, const CUtensorMap* m, int c0, int c1, int c2, uint32_t bar) {
    asm volatile("cp.async.bulk.tensor.3d.shared::cluster.global.mbarrier::complete_tx::bytes [%0], [%1, {%3, %4, %5}], [%2];"
                 ::"r"(dst), "l"(m), "r"(bar), "r"(c0), "r"(c1), "r"(c2) : "memory");
}
__device__ __forceinline__ void tma2_mc(uint32_t dst, const CUtensorMap* m, int c0, int c1, uint32_t bar) {
    asm volatile("cp.async.bulk.tensor.2d.shared::cluster.global.mbarrier::complete_tx::bytes.multicast::cluster [%0], [%1, {%3, %4}], [%2], %5;"
                 ::"r"(dst), "l"(m), "r"(bar), "r"(c0), "r"(c1), "h"((uint16_t)3) : "memory");
}
__device__ __forceinline__ void tma3_mc(uint32_t dst, const CUtensorMap* m, int c0, int c1, int c2, uint32_t bar) {
    asm volatile("cp.async.bulk.tensor.3d.shared::cluster.global.mbarrier::complete_tx::bytes.multicast::cluster [%0], [%1, {%3, %4, %5}], [%2], %6;"
                 ::"r"(dst), "l"(m), "r"(bar), "r"(c0), "r"(c1), "r"(c2), "h"((uint16_t)3) : "memory");
}
__device__ __forceinline__ void prefetch_map(const CUtensorMap* m) { asm volatile("prefetch.tensormap [%0];" ::"l"(m) : "memory"); }
__device__ __forceinline__ void prefetch_l2(const void* p, uint32_t bytes) {
    asm volatile("cp.async.bulk.prefetch.L2.global [%0], %1;" ::"l"(p), "r"(bytes) : "memory");
}
__device__ __forceinline__ void wg_fence() { asm volatile("wgmma.fence.sync.aligned;" ::: "memory"); }
__device__ __forceinline__ void wg_commit() { asm volatile("wgmma.commit_group.sync.aligned;" ::: "memory"); }
template <int N> __device__ __forceinline__ void wg_wait() { asm volatile("wgmma.wait_group.sync.aligned %0;" ::"n"(N) : "memory"); }
__device__ __forceinline__ unsigned ld_acquire(const unsigned* p) {
    unsigned v; asm volatile("ld.acquire.gpu.global.u32 %0, [%1];" : "=r"(v) : "l"(p) : "memory"); return v;
}
__device__ __forceinline__ void fence_gpu() { asm volatile("fence.acq_rel.gpu;" ::: "memory"); }
__device__ __forceinline__ void fence_async_global() { asm volatile("fence.proxy.async.global;" ::: "memory"); }
__device__ __forceinline__ void red_add(unsigned* p, unsigned v) { asm volatile("red.relaxed.gpu.global.add.u32 [%0], %1;" ::"l"(p), "r"(v) : "memory"); }
__device__ __forceinline__ void st_relaxed(unsigned* p, unsigned v) { asm volatile("st.relaxed.gpu.global.u32 [%0], %1;" ::"l"(p), "r"(v) : "memory"); }
__device__ __forceinline__ void poll_ge(const unsigned* p, unsigned target) {
    int it = 0;
#pragma unroll 1
    while ((int)(ld_acquire(p) - target) < 0) { if (++it > (1 << 16)) break; }
}
template <int ID, int N> __device__ __forceinline__ void bar_sync() { asm volatile("bar.sync %0, %1;" ::"n"(ID), "n"(N) : "memory"); }
__device__ __forceinline__ float ex2(float x) { float y; asm("ex2.approx.ftz.f32 %0, %1;" : "=f"(y) : "f"(x)); return y; }
__device__ __forceinline__ float rcp(float x) { float y; asm("rcp.approx.ftz.f32 %0, %1;" : "=f"(y) : "f"(x)); return y; }
__device__ __forceinline__ uint32_t pack2(float lo, float hi) {
    uint32_t r; asm("cvt.rn.bf16x2.f32 %0, %1, %2;" : "=r"(r) : "f"(hi), "f"(lo)); return r;
}
__device__ __forceinline__ float bf_lo(uint32_t v) { return __uint_as_float(v << 16); }
__device__ __forceinline__ float bf_hi(uint32_t v) { return __uint_as_float(v & 0xffff0000u); }
__device__ __forceinline__ float2 lds64(uint32_t a) { float2 v; asm volatile("ld.shared.v2.f32 {%0,%1}, [%2];" : "=f"(v.x), "=f"(v.y) : "r"(a)); return v; }
__device__ __forceinline__ void mma16(float (&c)[4], uint32_t a0, uint32_t a1, uint32_t a2, uint32_t a3, uint32_t b0, uint32_t b1) {
    asm("mma.sync.aligned.m16n8k16.row.col.f32.bf16.bf16.f32 {%0,%1,%2,%3}, {%4,%5,%6,%7}, {%8,%9}, {%0,%1,%2,%3};"
        : "+f"(c[0]), "+f"(c[1]), "+f"(c[2]), "+f"(c[3]) : "r"(a0), "r"(a1), "r"(a2), "r"(a3), "r"(b0), "r"(b1));
}
__device__ __forceinline__ void mma8(float (&c)[4], uint32_t a0, uint32_t a1, uint32_t b0) {
    asm("mma.sync.aligned.m16n8k8.row.col.f32.bf16.bf16.f32 {%0,%1,%2,%3}, {%4,%5}, {%6}, {%0,%1,%2,%3};"
        : "+f"(c[0]), "+f"(c[1]), "+f"(c[2]), "+f"(c[3]) : "r"(a0), "r"(a1), "r"(b0));
}
__device__ __forceinline__ uint32_t movm(uint32_t a) {
    uint32_t d; asm("movmatrix.sync.aligned.m8n8.trans.b16 %0, %1;" : "=r"(d) : "r"(a)); return d;
}

__device__ __forceinline__ void wgmma_n48(float (&d)[24], uint32_t alo, uint32_t ahi, uint32_t blo, uint32_t bhi, int sd) {
    asm volatile("{\n.reg .pred p;\n.reg .b64 da, db;\nsetp.ne.b32 p, %28, 0;\nmov.b64 da, {%24,%25};\nmov.b64 db, {%26,%27};\n"
        "wgmma.mma_async.sync.aligned.m64n48k16.f32.bf16.bf16 {"
        "%0,%1,%2,%3,%4,%5,%6,%7,%8,%9,%10,%11,%12,%13,%14,%15,"
        "%16,%17,%18,%19,%20,%21,%22,%23"
        "}, da, db, p, 1, 1, 0, 1;\n}\n"
        : "+f"(d[0]), "+f"(d[1]), "+f"(d[2]), "+f"(d[3]), "+f"(d[4]), "+f"(d[5]), "+f"(d[6]), "+f"(d[7]),
          "+f"(d[8]), "+f"(d[9]), "+f"(d[10]), "+f"(d[11]), "+f"(d[12]), "+f"(d[13]), "+f"(d[14]), "+f"(d[15]),
          "+f"(d[16]), "+f"(d[17]), "+f"(d[18]), "+f"(d[19]), "+f"(d[20]), "+f"(d[21]), "+f"(d[22]), "+f"(d[23])
        : "r"(alo), "r"(ahi), "r"(blo), "r"(bhi), "r"(sd));
}
__device__ __forceinline__ void wgmma_n128(float (&d)[64], uint32_t alo, uint32_t ahi, uint32_t blo, uint32_t bhi, int sd) {
    asm volatile("{\n.reg .pred p;\n.reg .b64 da, db;\nsetp.ne.b32 p, %68, 0;\nmov.b64 da, {%64,%65};\nmov.b64 db, {%66,%67};\n"
        "wgmma.mma_async.sync.aligned.m64n128k16.f32.bf16.bf16 {"
        "%0,%1,%2,%3,%4,%5,%6,%7,%8,%9,%10,%11,%12,%13,%14,%15,"
        "%16,%17,%18,%19,%20,%21,%22,%23,%24,%25,%26,%27,%28,%29,%30,%31,"
        "%32,%33,%34,%35,%36,%37,%38,%39,%40,%41,%42,%43,%44,%45,%46,%47,"
        "%48,%49,%50,%51,%52,%53,%54,%55,%56,%57,%58,%59,%60,%61,%62,%63"
        "}, da, db, p, 1, 1, 0, 1;\n}\n"
        : "+f"(d[0]), "+f"(d[1]), "+f"(d[2]), "+f"(d[3]), "+f"(d[4]), "+f"(d[5]), "+f"(d[6]), "+f"(d[7]),
          "+f"(d[8]), "+f"(d[9]), "+f"(d[10]), "+f"(d[11]), "+f"(d[12]), "+f"(d[13]), "+f"(d[14]), "+f"(d[15]),
          "+f"(d[16]), "+f"(d[17]), "+f"(d[18]), "+f"(d[19]), "+f"(d[20]), "+f"(d[21]), "+f"(d[22]), "+f"(d[23]),
          "+f"(d[24]), "+f"(d[25]), "+f"(d[26]), "+f"(d[27]), "+f"(d[28]), "+f"(d[29]), "+f"(d[30]), "+f"(d[31]),
          "+f"(d[32]), "+f"(d[33]), "+f"(d[34]), "+f"(d[35]), "+f"(d[36]), "+f"(d[37]), "+f"(d[38]), "+f"(d[39]),
          "+f"(d[40]), "+f"(d[41]), "+f"(d[42]), "+f"(d[43]), "+f"(d[44]), "+f"(d[45]), "+f"(d[46]), "+f"(d[47]),
          "+f"(d[48]), "+f"(d[49]), "+f"(d[50]), "+f"(d[51]), "+f"(d[52]), "+f"(d[53]), "+f"(d[54]), "+f"(d[55]),
          "+f"(d[56]), "+f"(d[57]), "+f"(d[58]), "+f"(d[59]), "+f"(d[60]), "+f"(d[61]), "+f"(d[62]), "+f"(d[63])
        : "r"(alo), "r"(ahi), "r"(blo), "r"(bhi), "r"(sd));
}
__device__ __forceinline__ void wgmma_n160(float (&d)[80], uint32_t alo, uint32_t ahi, uint32_t blo, uint32_t bhi, int sd) {
    asm volatile("{\n.reg .pred p;\n.reg .b64 da, db;\nsetp.ne.b32 p, %84, 0;\nmov.b64 da, {%80,%81};\nmov.b64 db, {%82,%83};\n"
        "wgmma.mma_async.sync.aligned.m64n160k16.f32.bf16.bf16 {"
        "%0,%1,%2,%3,%4,%5,%6,%7,%8,%9,%10,%11,%12,%13,%14,%15,"
        "%16,%17,%18,%19,%20,%21,%22,%23,%24,%25,%26,%27,%28,%29,%30,%31,"
        "%32,%33,%34,%35,%36,%37,%38,%39,%40,%41,%42,%43,%44,%45,%46,%47,"
        "%48,%49,%50,%51,%52,%53,%54,%55,%56,%57,%58,%59,%60,%61,%62,%63,"
        "%64,%65,%66,%67,%68,%69,%70,%71,%72,%73,%74,%75,%76,%77,%78,%79"
        "}, da, db, p, 1, 1, 0, 1;\n}\n"
        : "+f"(d[0]), "+f"(d[1]), "+f"(d[2]), "+f"(d[3]), "+f"(d[4]), "+f"(d[5]), "+f"(d[6]), "+f"(d[7]),
          "+f"(d[8]), "+f"(d[9]), "+f"(d[10]), "+f"(d[11]), "+f"(d[12]), "+f"(d[13]), "+f"(d[14]), "+f"(d[15]),
          "+f"(d[16]), "+f"(d[17]), "+f"(d[18]), "+f"(d[19]), "+f"(d[20]), "+f"(d[21]), "+f"(d[22]), "+f"(d[23]),
          "+f"(d[24]), "+f"(d[25]), "+f"(d[26]), "+f"(d[27]), "+f"(d[28]), "+f"(d[29]), "+f"(d[30]), "+f"(d[31]),
          "+f"(d[32]), "+f"(d[33]), "+f"(d[34]), "+f"(d[35]), "+f"(d[36]), "+f"(d[37]), "+f"(d[38]), "+f"(d[39]),
          "+f"(d[40]), "+f"(d[41]), "+f"(d[42]), "+f"(d[43]), "+f"(d[44]), "+f"(d[45]), "+f"(d[46]), "+f"(d[47]),
          "+f"(d[48]), "+f"(d[49]), "+f"(d[50]), "+f"(d[51]), "+f"(d[52]), "+f"(d[53]), "+f"(d[54]), "+f"(d[55]),
          "+f"(d[56]), "+f"(d[57]), "+f"(d[58]), "+f"(d[59]), "+f"(d[60]), "+f"(d[61]), "+f"(d[62]), "+f"(d[63]),
          "+f"(d[64]), "+f"(d[65]), "+f"(d[66]), "+f"(d[67]), "+f"(d[68]), "+f"(d[69]), "+f"(d[70]), "+f"(d[71]),
          "+f"(d[72]), "+f"(d[73]), "+f"(d[74]), "+f"(d[75]), "+f"(d[76]), "+f"(d[77]), "+f"(d[78]), "+f"(d[79])
        : "r"(alo), "r"(ahi), "r"(blo), "r"(bhi), "r"(sd));
}
__device__ __forceinline__ void wgmma_n192(float (&d)[96], uint32_t alo, uint32_t ahi, uint32_t blo, uint32_t bhi, int sd) {
    asm volatile("{\n.reg .pred p;\n.reg .b64 da, db;\nsetp.ne.b32 p, %100, 0;\nmov.b64 da, {%96,%97};\nmov.b64 db, {%98,%99};\n"
        "wgmma.mma_async.sync.aligned.m64n192k16.f32.bf16.bf16 {"
        "%0,%1,%2,%3,%4,%5,%6,%7,%8,%9,%10,%11,%12,%13,%14,%15,"
        "%16,%17,%18,%19,%20,%21,%22,%23,%24,%25,%26,%27,%28,%29,%30,%31,"
        "%32,%33,%34,%35,%36,%37,%38,%39,%40,%41,%42,%43,%44,%45,%46,%47,"
        "%48,%49,%50,%51,%52,%53,%54,%55,%56,%57,%58,%59,%60,%61,%62,%63,"
        "%64,%65,%66,%67,%68,%69,%70,%71,%72,%73,%74,%75,%76,%77,%78,%79,"
        "%80,%81,%82,%83,%84,%85,%86,%87,%88,%89,%90,%91,%92,%93,%94,%95"
        "}, da, db, p, 1, 1, 0, 1;\n}\n"
        : "+f"(d[0]), "+f"(d[1]), "+f"(d[2]), "+f"(d[3]), "+f"(d[4]), "+f"(d[5]), "+f"(d[6]), "+f"(d[7]),
          "+f"(d[8]), "+f"(d[9]), "+f"(d[10]), "+f"(d[11]), "+f"(d[12]), "+f"(d[13]), "+f"(d[14]), "+f"(d[15]),
          "+f"(d[16]), "+f"(d[17]), "+f"(d[18]), "+f"(d[19]), "+f"(d[20]), "+f"(d[21]), "+f"(d[22]), "+f"(d[23]),
          "+f"(d[24]), "+f"(d[25]), "+f"(d[26]), "+f"(d[27]), "+f"(d[28]), "+f"(d[29]), "+f"(d[30]), "+f"(d[31]),
          "+f"(d[32]), "+f"(d[33]), "+f"(d[34]), "+f"(d[35]), "+f"(d[36]), "+f"(d[37]), "+f"(d[38]), "+f"(d[39]),
          "+f"(d[40]), "+f"(d[41]), "+f"(d[42]), "+f"(d[43]), "+f"(d[44]), "+f"(d[45]), "+f"(d[46]), "+f"(d[47]),
          "+f"(d[48]), "+f"(d[49]), "+f"(d[50]), "+f"(d[51]), "+f"(d[52]), "+f"(d[53]), "+f"(d[54]), "+f"(d[55]),
          "+f"(d[56]), "+f"(d[57]), "+f"(d[58]), "+f"(d[59]), "+f"(d[60]), "+f"(d[61]), "+f"(d[62]), "+f"(d[63]),
          "+f"(d[64]), "+f"(d[65]), "+f"(d[66]), "+f"(d[67]), "+f"(d[68]), "+f"(d[69]), "+f"(d[70]), "+f"(d[71]),
          "+f"(d[72]), "+f"(d[73]), "+f"(d[74]), "+f"(d[75]), "+f"(d[76]), "+f"(d[77]), "+f"(d[78]), "+f"(d[79]),
          "+f"(d[80]), "+f"(d[81]), "+f"(d[82]), "+f"(d[83]), "+f"(d[84]), "+f"(d[85]), "+f"(d[86]), "+f"(d[87]),
          "+f"(d[88]), "+f"(d[89]), "+f"(d[90]), "+f"(d[91]), "+f"(d[92]), "+f"(d[93]), "+f"(d[94]), "+f"(d[95])
        : "r"(alo), "r"(ahi), "r"(blo), "r"(bhi), "r"(sd));
}

constexpr uint32_t HI_128 = 0x40000040u;
constexpr uint32_t HI_32 = 0xC0000010u;
__device__ __forceinline__ constexpr uint32_t lbo(uint32_t bytes) { return (bytes >> 4) << 16; }

struct Ctx {
    uint32_t sb;
    uint32_t bar;
    uint32_t rbar;
    uint32_t a_lo;
    uint32_t b_lo;
    int lane, q, g, w, par;
    int tile, slot;
    float m0, m1, r0, r1;
};

__device__ __forceinline__ void arrive_both(const Ctx& c, int bar_idx) {
    if (c.lane < 2) mbar_arrive_cluster(c.rbar + bar_idx * 8);
}
__device__ __forceinline__ void arrive_local(const Ctx& c, int bar_idx) {
    __syncwarp();
    if (c.lane == 0) mbar_arrive(c.bar + bar_idx * 8);
}

__device__ __forceinline__ void store_pair(__nv_bfloat16* rowp  , int q, uint32_t a, uint32_t b) {
    const bool odd = q & 1;
    uint32_t send = odd ? a : b;
    uint32_t recv = __shfl_xor_sync(0xffffffffu, send, 1);
    uint2 v;
    v.x = odd ? recv : a;
    v.y = odd ? b : recv;
    *reinterpret_cast<uint2*>(rowp + (odd ? 8 + 2 * (q - 1) : 2 * q)) = v;
}

__device__ __forceinline__ void ln_pack(const Ctx& c, const float* a, int col, uint32_t& lo, uint32_t& hi) {
    float2 cs = lds64(c.sb + SM_CS + (col + 2 * c.q) * 4);
    lo = pack2(fmaf(-c.m0, cs.x, a[0]) * c.r0, fmaf(-c.m0, cs.y, a[1]) * c.r0);
    hi = pack2(fmaf(-c.m1, cs.x, a[2]) * c.r1, fmaf(-c.m1, cs.y, a[3]) * c.r1);
}
template <int PART, int G0, int G1>
__device__ __forceinline__ void qkv_pack(const Ctx& c, const float (&a1)[96], const float (&a2)[24], uint32_t (&dst)[20]) {
#pragma unroll
    for (int G = G0; G < G1; G++) {
        if (G < 8) ln_pack(c, &a1[PART * 32 + G * 4], PART * 64 + G * 8, dst[2 * G], dst[2 * G + 1]);
        else ln_pack(c, &a2[PART * 8 + (G - 8) * 4], 192 + PART * 16 + (G - 8) * 8, dst[2 * G], dst[2 * G + 1]);
    }
}

template <int H>
__device__ __forceinline__ void attn_head(const Ctx& c, bool first, const uint32_t (&qp)[20], const uint32_t (&kp)[20], const uint32_t (&vp)[20],
                                          const uint32_t (&hk)[10], const uint32_t (&hv)[10], uint32_t (&op)[20]) {
    constexpr int GA = (H == 0) ? 0 : (H == 1) ? 3 : (H == 2) ? 5 : 8;
    constexpr int GS = (H < 2) ? 2 : 7;
    const bool mine = (H & 1) ? (c.q >= 2) : (c.q < 2);
    const uint32_t qs0 = mine ? qp[2 * GS] : 0u, qs1 = mine ? qp[2 * GS + 1] : 0u;
    float sP[4] = {0.f, 0.f, 0.f, 0.f}, sL[4] = {0.f, 0.f, 0.f, 0.f}, sU[4] = {0.f, 0.f, 0.f, 0.f};
    mma16(sP, qp[2 * GA], qp[2 * GA + 1], qp[2 * GA + 2], qp[2 * GA + 3], hk[GA], hk[GA + 1]);
    mma16(sL, qp[2 * GA], qp[2 * GA + 1], qp[2 * GA + 2], qp[2 * GA + 3], kp[2 * GA], kp[2 * GA + 2]);
    mma16(sU, qp[2 * GA], qp[2 * GA + 1], qp[2 * GA + 2], qp[2 * GA + 3], kp[2 * GA + 1], kp[2 * GA + 3]);
    mma8(sP, qs0, qs1, hk[GS]);
    mma8(sL, qs0, qs1, kp[2 * GS]);
    mma8(sU, qs0, qs1, kp[2 * GS + 1]);
    const bool gt0 = 2 * c.q > c.g, gt1 = 2 * c.q + 1 > c.g;
    const float ninf = __int_as_float(0xff800000);
    float l0 = gt0 ? (first ? ninf : sP[0]) : sL[0];
    float l1 = gt1 ? (first ? ninf : sP[1]) : sL[1];
    float u0 = gt0 ? sL[2] : sU[2];
    float u1 = gt1 ? sL[3] : sU[3];
    float ml = fmaxf(l0, l1), mu = fmaxf(u0, u1);
    ml = fmaxf(ml, __shfl_xor_sync(0xffffffffu, ml, 1));
    mu = fmaxf(mu, __shfl_xor_sync(0xffffffffu, mu, 1));
    ml = fmaxf(ml, __shfl_xor_sync(0xffffffffu, ml, 2));
    mu = fmaxf(mu, __shfl_xor_sync(0xffffffffu, mu, 2));
    constexpr float kScale = 0.22360679774997896f * 1.4426950408889634f;
    l0 = ex2((l0 - ml) * kScale); l1 = ex2((l1 - ml) * kScale);
    u0 = ex2((u0 - mu) * kScale); u1 = ex2((u1 - mu) * kScale);
    float sl = l0 + l1, su = u0 + u1;
    sl += __shfl_xor_sync(0xffffffffu, sl, 1);
    su += __shfl_xor_sync(0xffffffffu, su, 1);
    sl += __shfl_xor_sync(0xffffffffu, sl, 2);
    su += __shfl_xor_sync(0xffffffffu, su, 2);
    const float il = rcp(sl), iu = rcp(su);
    l0 *= il; l1 *= il; u0 *= iu; u1 *= iu;
    const uint32_t pLoP = pack2(gt0 ? l0 : 0.f, gt1 ? l1 : 0.f);
    const uint32_t pLoL = pack2(gt0 ? 0.f : l0, gt1 ? 0.f : l1);
    const uint32_t pUpL = pack2(gt0 ? u0 : 0.f, gt1 ? u1 : 0.f);
    const uint32_t pUpU = pack2(gt0 ? 0.f : u0, gt1 ? 0.f : u1);
#pragma unroll
    for (int t = 0; t < 3; t++) {
        const int G = (t < 2) ? GA + t : GS;
        float o[4] = {0.f, 0.f, 0.f, 0.f};
        mma16(o, pLoP, 0u, pLoL, pUpL, movm(hv[G]), movm(vp[2 * G]));
        mma8(o, 0u, pUpU, movm(vp[2 * G + 1]));
        const uint32_t lo = pack2(o[0], o[1]), hi = pack2(o[2], o[3]);
        if (t < 2 || (H & 1) == 0) { op[2 * G] = lo; op[2 * G + 1] = hi; }
        else { op[2 * G] = mine ? lo : op[2 * G]; op[2 * G + 1] = mine ? hi : op[2 * G + 1]; }
    }
}

template <int R>
__device__ __forceinline__ void swiglu_group(const Ctx& c, const float (&acc)[64], int G, uint32_t& lo, uint32_t& hi) {
    const uint32_t csb = c.sb + SM_CS + (240 + R * 128 + G * 8 + 2 * c.q) * 4;
    const float2 cg = lds64(csb), cu = lds64(csb + 256);
    float h[4];
#pragma unroll
    for (int e = 0; e < 4; e++) {
        const float m = (e < 2) ? c.m0 : c.m1, r = (e < 2) ? c.r0 : c.r1;
        const float gate = fmaf(-m, (e & 1) ? cg.y : cg.x, acc[4 * G + e]) * r;
        const float up = fmaf(-m, (e & 1) ? cu.y : cu.x, acc[32 + 4 * G + e]) * r;
        const float sg = rcp(1.f + ex2(gate * -1.4426950408889634f));
        h[e] = gate * sg * up;
    }
    lo = pack2(h[0], h[1]);
    hi = pack2(h[2], h[3]);
}
template <int R>
__device__ __forceinline__ void swiglu_pair(const Ctx& c, const float (&acc)[64], int P, __nv_bfloat16* hrow) {
    uint32_t a0, a1, b0, b1;
    swiglu_group<R>(c, acc, 2 * P, a0, a1);
    swiglu_group<R>(c, acc, 2 * P + 1, b0, b1);
    store_pair(hrow + 16 * P, c.q, a0, b0);
    store_pair(hrow + 8 * kActLd + 16 * P, c.q, a1, b1);
}

template <int N>
__device__ __forceinline__ void f_issue(const Ctx& c, float (&acc)[64]) {
    constexpr int S = (N - 20) % 10, SLOT = N & 3;
    mbar_wait(c.bar + (B_RFULL + SLOT) * 8, (N >> 2) & 1);
    wg_fence();
#pragma unroll
    for (int kk = 0; kk < 4; kk++)
        wgmma_n128(acc, c.a_lo + S * 1024 + kk * 2, HI_128, c.b_lo + lbo(8192) + SLOT * 1024 + kk * 128, HI_128, (S | kk) != 0);
    wg_commit();
    wg_wait<1>();
    if (N - 1 <= 45) arrive_both(c, B_REMPTY + ((N - 1) & 3));
    if (N == 43) arrive_both(c, B_GEMPTY + 0);
    if (N == 45) arrive_both(c, B_GEMPTY + 1);
    if (N == 48) arrive_both(c, B_GEMPTY + 2);
}

__device__ __forceinline__ void g_issue(const Ctx& c, float (&acc)[80], int slot, int parity, bool first) {
    mbar_wait(c.bar + (B_GFULL + slot) * 8, parity);
    wg_fence();
    const uint32_t st = ((c.sb & 0x3FFFF) >> 4) + slot * (G_STAGE >> 4);
    const uint32_t alo = st + c.par * 512 + lbo(16), blo = st + 1024 + lbo(4096);
#pragma unroll
    for (int kk = 0; kk < 4; kk++)
        wgmma_n160(acc, alo + kk * 2, HI_128, blo + (kk >> 1) * 768 + (kk & 1) * 128, HI_128, !(first && kk == 0));
    wg_commit();
}

}

__global__ void __cluster_dims__(2, 1, 1) __launch_bounds__(384, 1)
fused_block_kernel(const __grid_constant__ Maps maps, const __nv_bfloat16* __restrict__ x, const __nv_bfloat16* __restrict__ wqkv,
                   const __nv_bfloat16* __restrict__ w1, const __nv_bfloat16* __restrict__ w3, const __nv_bfloat16* __restrict__ wo,
                   const __nv_bfloat16* __restrict__ w2, __nv_bfloat16* __restrict__ out) {
    extern __shared__ __align__(1024) uint8_t smem_raw[];
    const uint32_t sb = smem_u32(smem_raw);
    const int warp = __shfl_sync(0xffffffffu, threadIdx.x >> 5, 0);
    const int lane = threadIdx.x & 31;
    uint32_t rank;
    asm("mov.u32 %0, %%cluster_ctarank;" : "=r"(rank));
    const int pair = blockIdx.x >> 1;
    const int slot = pair & 7;
    const int tile = (pair >> 3) * 2 + rank;
    const int jj = slot & 3;
    const bool typeL = slot >= 4;

    if (warp == 8) {
        TRACE(0);
        for (int b = lane; b < B_COUNT; b += 32) {
            uint32_t cnt = 1;
            if ((b >= B_REMPTY && b < B_GFULL) || (b >= B_GEMPTY && b < B_CS)) cnt = 16;
            else if (b == B_HALOW) cnt = 2;
            else if (b == B_HALOR || b == B_HALOR + 1) cnt = 5;
            else if (b >= B_WDONE && b < B_PART) cnt = 8;
            mbar_init(sb + SM_BAR + b * 8, cnt);
        }
        asm volatile("fence.mbarrier_init.release.cluster;" ::: "memory");
        __syncwarp();
        if (elect_one()) {
            prefetch_map(&maps.x); prefetch_map(&maps.wq); prefetch_map(&maps.wqr);
            mbar_expect_tx(sb + SM_BAR + B_XFULL * 8, 16384);
            tma3(sb + SM_X, &maps.x, 0, tile * 64, 0, sb + SM_BAR + B_XFULL * 8);
        }
    } else if (warp == 9) {
        asm volatile("st.shared.u32 [%0], %1;" ::"r"(sb + SM_CSACC + lane * 4), "r"(0) : "memory");
    }
    __syncthreads();
    asm volatile("barrier.cluster.arrive.relaxed.aligned;\nbarrier.cluster.wait.aligned;" ::: "memory");

    if (warp >= 8) {
        asm volatile("setmaxnreg.dec.sync.aligned.u32 56;");
        const uint32_t bar = launder(sb + SM_BAR);
        if (warp == 8) {
            const uint32_t ring = launder(sb + SM_RING);
            if (elect_one()) {
#pragma unroll 1
                for (int n = 0; n < 4; n++) {
                    mbar_expect_tx(bar + (B_RFULL + n) * 8, 15360);
                    tma3_mc(ring + n * 16384 + rank * 6144, &maps.wq, 80 * slot, 32 * n + 16 * rank, 0, bar + (B_RFULL + n) * 8);
                    tma3_mc(ring + n * 16384 + 12288 + rank * 1536, &maps.wqr, 80 * slot + 64, 32 * n + 16 * rank, 0, bar + (B_RFULL + n) * 8);
                    if (n < 3) {
#pragma unroll 1
                        for (int c = 1 + 3 * n; c < 4 + 3 * n; c++) {
                            mbar_expect_tx(bar + (B_XFULL + c) * 8, 16384);
                            tma3(sb + SM_X + c * 16384, &maps.x, c * 64, tile * 64, 0, bar + (B_XFULL + c) * 8);
                        }
                    }
                }
                prefetch_map(&maps.w1); prefetch_map(&maps.w3); prefetch_map(&maps.act);
                prefetch_map(&maps.wo2); prefetch_map(&maps.wo1); prefetch_map(&maps.w22); prefetch_map(&maps.w21);
            }
            __syncwarp();
            TRACE(1);
#pragma unroll 1
            for (int n = 4; n < 20; n++) {
                const int s = n & 3;
                mbar_wait(bar + (B_REMPTY + s) * 8, ((n >> 2) - 1) & 1);
                if (elect_one()) {
                    mbar_expect_tx(bar + (B_RFULL + s) * 8, 15360);
                    tma3_mc(ring + s * 16384 + rank * 6144, &maps.wq, 80 * slot, 32 * n + 16 * rank, 0, bar + (B_RFULL + s) * 8);
                    tma3_mc(ring + s * 16384 + 12288 + rank * 1536, &maps.wqr, 80 * slot + 64, 32 * n + 16 * rank, 0, bar + (B_RFULL + s) * 8);
                }
            }
            const CUtensorMap* mf = rank ? &maps.w3 : &maps.w1;
            {
                int col = 64 * slot, k = 0;
#pragma unroll 1
                for (int n = 20; n < 50; n++) {
                    const int s = n & 3;
                    mbar_wait(bar + (B_REMPTY + s) * 8, ((n >> 2) - 1) & 1);
                    if (elect_one()) {
                        mbar_expect_tx(bar + (B_RFULL + s) * 8, 16384);
                        tma2_mc(ring + s * 16384 + rank * 8192, mf, col, k, bar + (B_RFULL + s) * 8);
                    }
                    k += 64;
                    if (k == 640) { k = 0; col += 512; }
                }
            }
            TRACE(2);
            unsigned epoch;
            asm volatile("ld.shared.u32 %0, [%1];" : "=r"(epoch) : "r"(sb + SM_EPOCH) : "memory");
            const unsigned tgt = (epoch + 1) * 8;
            const int nt = typeL ? NT_L : NT_E;
            int s = 0, ph = 0;
#pragma unroll 1
            for (int t = 0; t < nt; t++) {
                mbar_wait(bar + (B_GEMPTY + s) * 8, ph);
                int kc;
                const unsigned* flag = nullptr;
                if (typeL) {
                    kc = (t < 11) ? 7 + t : 15 + t;
                    if (t == 0) flag = &g_cntO[tile * 32];
                    if (t == 3) flag = &g_cntH[(tile * 3 + 0) * 32];
                    if (t == 11) flag = &g_cntH[(tile * 3 + 2) * 32];
                } else {
                    kc = (t < 7) ? t : 11 + t;
                    if (t == 0) flag = &g_cntO[tile * 32];
                    if (t == 7) flag = &g_cntH[(tile * 3 + 1) * 32];
                }
                if (elect_one()) {
                    if (flag) { poll_ge(flag, tgt); fence_async_global(); }
                    const uint32_t st = sb + s * G_STAGE, fb = bar + (B_GFULL + s) * 8;
                    mbar_expect_tx(fb, 16384 + 20480);
                    tma2(st, &maps.act, kc * 64, tile * 128, fb);
                    const bool isO = kc < 10;
                    const int k0 = (isO ? kc : kc - 10) * 64 + 32 * rank;
                    tma3_mc(st + 16384 + rank * 12288, isO ? &maps.wo2 : &maps.w22, 160 * jj, k0, 0, fb);
                    tma2_mc(st + 16384 + rank * 12288 + 8192, isO ? &maps.wo1 : &maps.w21, 160 * jj + 128, k0, fb);
                }
                if (++s == 5) { s = 0; ph ^= 1; }
            }
            TRACE(3);
        } else {
            const int a = warp - 9;
            const int b = blockIdx.x;
            unsigned epoch = 0;
            if (a == 0) {
                if (lane == 0) {
                    epoch = ld_acquire(&g_cntA[0]) / kSetupArrivals;
                    asm volatile("st.shared.u32 [%0], %1;" ::"r"(sb + SM_EPOCH), "r"(epoch) : "memory");
                }
                epoch = __shfl_sync(0xffffffffu, epoch, 0);
            }
#pragma unroll 1
            for (int p = a; p < 8; p += 3) {
                const int row = 16 * b + 2 * p + (lane >> 4);
                const uint4* src = reinterpret_cast<const uint4*>(x + (size_t)row * kD) + (lane & 15);
                uint4 v[5];
#pragma unroll
                for (int u = 0; u < 5; u++) v[u] = __ldg(src + 16 * u);
                float s = 0.f;
#pragma unroll
                for (int u = 0; u < 5; u++)
                    s += (bf_lo(v[u].x) + bf_hi(v[u].x)) + (bf_lo(v[u].y) + bf_hi(v[u].y)) + (bf_lo(v[u].z) + bf_hi(v[u].z)) + (bf_lo(v[u].w) + bf_hi(v[u].w));
#pragma unroll
                for (int o = 1; o < 16; o <<= 1) s += __shfl_xor_sync(0xffffffffu, s, o);
                const float mean = s * (1.f / kD);
                float ss = 0.f;
#pragma unroll
                for (int u = 0; u < 5; u++) {
                    const uint32_t wv[4] = {v[u].x, v[u].y, v[u].z, v[u].w};
#pragma unroll
                    for (int e = 0; e < 4; e++) {
                        const float d0 = bf_lo(wv[e]) - mean, d1 = bf_hi(wv[e]) - mean;
                        ss = fmaf(d0, d0, ss); ss = fmaf(d1, d1, ss);
                    }
                }
#pragma unroll
                for (int o = 1; o < 16; o <<= 1) ss += __shfl_xor_sync(0xffffffffu, ss, o);
                if ((lane & 15) == 0) g_stats[row] = make_float2(mean, 1.f / sqrtf(ss * (1.f / kD) + 1e-5f));
            }
#pragma unroll 1
            for (int u = b; u < kSetupArrivals; u += 128) {
                const __nv_bfloat16* wp; int ld;
                if (u < 60) { wp = wqkv + 32 * u; ld = 3 * kD; }
                else if (u < 108) { wp = w1 + 32 * (u - 60); ld = kF; }
                else { wp = w3 + 32 * (u - 108); ld = kF; }
                wp += (size_t)(lane >> 2) * ld + (lane & 3) * 8;
                float acc[8];
#pragma unroll
                for (int e = 0; e < 8; e++) acc[e] = 0.f;
#pragma unroll 1
                for (int t0 = a; t0 < 80; t0 += 27) {
                    uint4 v[9];
#pragma unroll
                    for (int t = 0; t < 9; t++) {
                        const int blk = t0 + 3 * t;
                        v[t] = (blk < 80) ? __ldg(reinterpret_cast<const uint4*>(wp + (size_t)blk * 8 * ld)) : make_uint4(0, 0, 0, 0);
                    }
#pragma unroll
                    for (int t = 0; t < 9; t++) {
                        acc[0] += bf_lo(v[t].x); acc[1] += bf_hi(v[t].x); acc[2] += bf_lo(v[t].y); acc[3] += bf_hi(v[t].y);
                        acc[4] += bf_lo(v[t].z); acc[5] += bf_hi(v[t].z); acc[6] += bf_lo(v[t].w); acc[7] += bf_hi(v[t].w);
                    }
                }
#pragma unroll
                for (int e = 0; e < 8; e++) {
                    acc[e] += __shfl_xor_sync(0xffffffffu, acc[e], 4);
                    acc[e] += __shfl_xor_sync(0xffffffffu, acc[e], 8);
                    acc[e] += __shfl_xor_sync(0xffffffffu, acc[e], 16);
                }
                if (lane < 4) {
#pragma unroll
                    for (int e = 0; e < 8; e++)
                        asm volatile("red.shared.add.f32 [%0], %1;" ::"r"(sb + SM_CSACC + (lane * 8 + e) * 4), "f"(acc[e]) : "memory");
                }
                bar_sync<1, 96>();
                if (a == 0) {
                    float v;
                    asm volatile("ld.shared.f32 %0, [%1];" : "=f"(v) : "r"(sb + SM_CSACC + lane * 4) : "memory");
                    asm volatile("st.shared.u32 [%0], %1;" ::"r"(sb + SM_CSACC + lane * 4), "r"(0) : "memory");
                    g_cs[32 * u + lane] = v;
                    __syncwarp();
                    if (lane == 0) { fence_gpu(); red_add(&g_cntA[0], 1); }
                }
                bar_sync<1, 96>();
            }
            if (a != 0) asm volatile("ld.shared.u32 %0, [%1];" : "=r"(epoch) : "r"(sb + SM_EPOCH) : "memory");
            const unsigned tag = epoch + 1;
            if (a == 0) {
                TRACE(4);
                if (lane == 0) poll_ge(&g_cntA[0], tag * kSetupArrivals);
                __syncwarp();
                TRACE(5);
#pragma unroll 1
                for (int n = lane; n < 624; n += 32) {
                    int src;
                    if (n < 192) src = (n >> 6) * 640 + 80 * slot + (n & 63);
                    else if (n < 240) src = ((n - 192) >> 4) * 640 + 80 * slot + 64 + ((n - 192) & 15);
                    else {
                        const int m = n - 240, r = m >> 7, e = m & 127;
                        src = ((e < 64) ? 1920 : 3456) + 64 * (8 * r + slot) + (e & 63);
                    }
                    const float v = __ldcg(&g_cs[src]);
                    asm volatile("st.shared.f32 [%0], %1;" ::"r"(sb + SM_CS + n * 4), "f"(v) : "memory");
                }
                __syncwarp();
                if (lane == 0) {
                    mbar_arrive(bar + B_CS * 8);
                    prefetch_l2(wo + (size_t)b * 5 * kD, 5 * kD * 2);
                    prefetch_l2(w2 + (size_t)b * 12 * kD, 12 * kD * 2);
                }
                if (typeL) {
                    if (lane == 0) { poll_ge(&g_flagPart[(tile * 4 + jj) * 32], tag); mbar_arrive(bar + B_PART * 8); }
                }
            } else if (a == 1) {
                mbar_wait(bar + B_HALOW * 8, 0);
                if (lane == 0) {
                    if (tile < 15) { fence_gpu(); st_relaxed(&g_flagHalo[(tile * 8 + slot) * 32], tag); }
                    if (tile > 0) poll_ge(&g_flagHalo[((tile - 1) * 8 + slot) * 32], tag);
                    mbar_arrive(bar + B_HALOR * 8);
                    mbar_arrive(bar + (B_HALOR + 1) * 8);
                }
            } else {
#pragma unroll 1
                for (int r = 0; r < 4; r++) {
                    mbar_wait(bar + (B_WDONE + r) * 8, 0);
                    unsigned* cnt = (r == 1) ? &g_cntO[tile * 32] : &g_cntH[(tile * 3 + (r == 0 ? 0 : r - 1)) * 32];
                    if (lane == 0) { fence_async_global(); fence_gpu(); red_add(cnt, 1); }
                }
                if (!typeL) {
                    mbar_wait(bar + (B_WDONE + 4) * 8, 0);
                    if (lane == 0) { fence_gpu(); st_relaxed(&g_flagPart[(tile * 4 + jj) * 32], tag); }
                }
            }
        }
    } else {
        asm volatile("setmaxnreg.inc.sync.aligned.u32 224;");
        Ctx c;
        c.sb = sb;
        c.bar = sb + SM_BAR;
        c.lane = lane; c.q = lane & 3; c.g = lane >> 2; c.w = warp & 3; c.par = warp >> 2;
        c.rbar = mapa(c.bar, lane & 1);
        c.a_lo = ((sb & 0x3FFFF) >> 4) + c.par * 512 + lbo(16);
        c.b_lo = ((sb + SM_RING) & 0x3FFFF) >> 4;
        c.tile = tile; c.slot = slot;
        const int idx0 = c.w * 16 + c.g;
        const int tok0 = tile * 128 + 2 * idx0 + c.par;
        __nv_bfloat16* actrow = g_act + (size_t)(tile * 128 + c.par * 64 + idx0) * kActLd;

        float q1[96], q2[24];
#pragma unroll
        for (int n = 0; n < 20; n++) {
            if ((n & 1) == 0) mbar_wait(c.bar + (B_XFULL + n / 2) * 8, 0);
            mbar_wait(c.bar + (B_RFULL + (n & 3)) * 8, (n >> 2) & 1);
            if (n == 0 && c.w == 0) TRACE(8 + c.par);
            wg_fence();
#pragma unroll
            for (int h = 0; h < 2; h++) {
                const uint32_t alo = c.a_lo + (n >> 1) * 1024 + ((n & 1) * 2 + h) * 2;
                wgmma_n192(q1, alo, HI_128, c.b_lo + lbo(2048) + (n & 3) * 1024 + h * 384, HI_128, (n | h) != 0);
                wgmma_n48(q2, alo, HI_128, c.b_lo + lbo(512) + (n & 3) * 1024 + 768 + h * 96, HI_32, (n | h) != 0);
            }
            wg_commit();
            wg_wait<1>();
            if (n > 0) arrive_both(c, B_REMPTY + ((n - 1) & 3));
            if (n == 17) {
                mbar_wait(c.bar + B_CS * 8, 0);
                const float2 s0 = __ldcg(&g_stats[tok0]), s1 = __ldcg(&g_stats[tok0 + 16]);
                c.m0 = s0.x; c.r0 = s0.y; c.m1 = s1.x; c.r1 = s1.y;
            }
        }
        if (c.w == 0) TRACE(10 + c.par);

        float accA[64], accB[64];
        uint32_t qp[20], kp[20], vp[20], hk[10], hv[10], op[20];
        const bool first = (tile == 0) && (c.w == 0);
        f_issue<20>(c, accA); qkv_pack<1, 0, 5>(c, q1, q2, kp);
        f_issue<21>(c, accA); qkv_pack<1, 5, 10>(c, q1, q2, kp);
        f_issue<22>(c, accA); qkv_pack<2, 0, 5>(c, q1, q2, vp);
        f_issue<23>(c, accA); qkv_pack<2, 5, 10>(c, q1, q2, vp);
        {
            const int dt = (c.w == 3) ? tile + 1 : tile, dw = (c.w + 1) & 3;
            if (dt < 16) {
                uint4* hp = g_halo + (size_t)(((dt * 8 + slot) * 2 + c.par) * 4 + dw) * 160 + lane;
                hp[0] = make_uint4(kp[1], kp[3], kp[5], kp[7]);
                hp[32] = make_uint4(kp[9], kp[11], kp[13], kp[15]);
                hp[64] = make_uint4(kp[17], kp[19], vp[1], vp[3]);
                hp[96] = make_uint4(vp[5], vp[7], vp[9], vp[11]);
                hp[128] = make_uint4(vp[13], vp[15], vp[17], vp[19]);
            }
            __syncwarp();
            if (lane == 0) {
                mbar_arrive(c.bar + (B_HALOR + c.par) * 8);
                if (c.w == 3) mbar_arrive(c.bar + B_HALOW * 8);
            }
        }
        f_issue<24>(c, accA); qkv_pack<0, 0, 5>(c, q1, q2, qp);
        f_issue<25>(c, accA); qkv_pack<0, 5, 10>(c, q1, q2, qp);
        f_issue<26>(c, accA);
        f_issue<27>(c, accA);
        f_issue<28>(c, accA);
        f_issue<29>(c, accA);
        if (c.w == 0) TRACE(12 + c.par);

        __nv_bfloat16* hrow0 = actrow + kD + 64 * slot;
        f_issue<30>(c, accB); swiglu_pair<0>(c, accA, 0, hrow0);
        f_issue<31>(c, accB); swiglu_pair<0>(c, accA, 1, hrow0);
        f_issue<32>(c, accB); swiglu_pair<0>(c, accA, 2, hrow0);
        f_issue<33>(c, accB); swiglu_pair<0>(c, accA, 3, hrow0);
        arrive_local(c, B_WDONE + 0);
        f_issue<34>(c, accB);
        {
            mbar_wait(c.bar + (B_HALOR + c.par) * 8, 0);
            const uint4* hp = g_halo + (size_t)(((tile * 8 + slot) * 2 + c.par) * 4 + c.w) * 160 + lane;
            uint4 t0 = make_uint4(0, 0, 0, 0), t1 = t0, t2 = t0, t3 = t0, t4 = t0;
            if (!first) { t0 = __ldcg(hp); t1 = __ldcg(hp + 32); t2 = __ldcg(hp + 64); t3 = __ldcg(hp + 96); t4 = __ldcg(hp + 128); }
            hk[0] = t0.x; hk[1] = t0.y; hk[2] = t0.z; hk[3] = t0.w; hk[4] = t1.x; hk[5] = t1.y; hk[6] = t1.z; hk[7] = t1.w;
            hk[8] = t2.x; hk[9] = t2.y; hv[0] = t2.z; hv[1] = t2.w; hv[2] = t3.x; hv[3] = t3.y; hv[4] = t3.z; hv[5] = t3.w;
            hv[6] = t4.x; hv[7] = t4.y; hv[8] = t4.z; hv[9] = t4.w;
        }
        f_issue<35>(c, accB); attn_head<0>(c, first, qp, kp, vp, hk, hv, op);
        f_issue<36>(c, accB); attn_head<1>(c, first, qp, kp, vp, hk, hv, op);
        f_issue<37>(c, accB); attn_head<2>(c, first, qp, kp, vp, hk, hv, op);
        f_issue<38>(c, accB); attn_head<3>(c, first, qp, kp, vp, hk, hv, op);
        f_issue<39>(c, accB);
        {
            __nv_bfloat16* orow = actrow + 80 * slot;
#pragma unroll
            for (int p = 0; p < 5; p++) {
                store_pair(orow + 16 * p, c.q, op[4 * p], op[4 * p + 2]);
                store_pair(orow + 8 * kActLd + 16 * p, c.q, op[4 * p + 1], op[4 * p + 3]);
            }
            arrive_local(c, B_WDONE + 1);
        }
        if (c.w == 0) TRACE(14 + c.par);

        f_issue<40>(c, accA);
        f_issue<41>(c, accA); swiglu_pair<1>(c, accB, 0, hrow0 + 512);
        f_issue<42>(c, accA);
        f_issue<43>(c, accA); swiglu_pair<1>(c, accB, 1, hrow0 + 512);
        f_issue<44>(c, accA);
        f_issue<45>(c, accA); swiglu_pair<1>(c, accB, 2, hrow0 + 512);
        f_issue<46>(c, accA);
        f_issue<47>(c, accA); swiglu_pair<1>(c, accB, 3, hrow0 + 512);
        arrive_local(c, B_WDONE + 2);
        f_issue<48>(c, accA);
        f_issue<49>(c, accA);
        if (c.w == 0) TRACE(16 + c.par);

        float accG[80];
        const int nt = typeL ? NT_L : NT_E;
        g_issue(c, accG, 0, 0, true);
        wg_wait<1>();
        arrive_both(c, B_GEMPTY + 3);
        arrive_both(c, B_GEMPTY + 4);
        swiglu_pair<2>(c, accA, 0, hrow0 + 1024);
        g_issue(c, accG, 1, 0, false); wg_wait<1>(); arrive_both(c, B_GEMPTY + 0);
        swiglu_pair<2>(c, accA, 1, hrow0 + 1024);
        g_issue(c, accG, 2, 0, false); wg_wait<1>(); arrive_both(c, B_GEMPTY + 1);
        swiglu_pair<2>(c, accA, 2, hrow0 + 1024);
        g_issue(c, accG, 3, 0, false); wg_wait<1>(); arrive_both(c, B_GEMPTY + 2);
        swiglu_pair<2>(c, accA, 3, hrow0 + 1024);
        arrive_local(c, B_WDONE + 3);
        g_issue(c, accG, 4, 0, false); wg_wait<1>(); arrive_both(c, B_GEMPTY + 3);
        {
            int s = 0, ph = 1;
#pragma unroll 1
            for (int t = 5; t < nt; t++) {
                g_issue(c, accG, s, ph, false);
                wg_wait<1>();
                if (t + 4 < nt) arrive_both(c, B_GEMPTY + (s == 0 ? 4 : s - 1));
                if (++s == 5) { s = 0; ph ^= 1; }
            }
        }
        if (c.w == 0) TRACE(18 + c.par);
        const int tid = threadIdx.x;
        float4* pp = g_part + (size_t)(tile * 4 + jj) * 20 * 256 + tid;
        if (!typeL) {
            const uint32_t* xr0 = reinterpret_cast<const uint32_t*>(x + (size_t)tok0 * kD + 160 * jj + 2 * c.q);
            uint32_t xa[20], xb[20];
#pragma unroll
            for (int G = 0; G < 20; G++) { xa[G] = __ldg(xr0 + 4 * G); xb[G] = __ldg(xr0 + 16 * (kD / 2) + 4 * G); }
            wg_wait<0>();
#pragma unroll
            for (int G = 0; G < 20; G++)
                pp[G * 256] = make_float4(accG[4 * G] + bf_lo(xa[G]), accG[4 * G + 1] + bf_hi(xa[G]),
                                          accG[4 * G + 2] + bf_lo(xb[G]), accG[4 * G + 3] + bf_hi(xb[G]));
            arrive_local(c, B_WDONE + 4);
        } else {
            mbar_wait(c.bar + B_PART * 8, 0);
            float4 pv[20];
#pragma unroll
            for (int G = 0; G < 20; G++) pv[G] = __ldcg(pp + G * 256);
            wg_wait<0>();
            __nv_bfloat16* orow = out + (size_t)tok0 * kD + 160 * jj;
#pragma unroll
            for (int p = 0; p < 10; p++) {
                const int G = 2 * p;
                const uint32_t a0 = pack2(accG[4 * G] + pv[G].x, accG[4 * G + 1] + pv[G].y);
                const uint32_t a1 = pack2(accG[4 * G + 2] + pv[G].z, accG[4 * G + 3] + pv[G].w);
                const uint32_t b0 = pack2(accG[4 * G + 4] + pv[G + 1].x, accG[4 * G + 5] + pv[G + 1].y);
                const uint32_t b1 = pack2(accG[4 * G + 6] + pv[G + 1].z, accG[4 * G + 7] + pv[G + 1].w);
                store_pair(orow + 16 * p, c.q, a0, b0);
                store_pair(orow + 16 * kD + 16 * p, c.q, a1, b1);
            }
        }
        if (c.w == 0) TRACE(20 + c.par);
    }
}

namespace {
typedef CUresult (*EncodeFn)(CUtensorMap*, CUtensorMapDataType, cuuint32_t, void*, const cuuint64_t*, const cuuint64_t*, const cuuint32_t*,
                             const cuuint32_t*, CUtensorMapInterleave, CUtensorMapSwizzle, CUtensorMapL2promotion, CUtensorMapFloatOOBfill);

bool encode(EncodeFn fn, CUtensorMap* m, const void* ptr, int rank, const cuuint64_t* dims, const cuuint64_t* strides, const cuuint32_t* box,
            CUtensorMapSwizzle sw) {
    const cuuint32_t es[3] = {1, 1, 1};
    return fn(m, CU_TENSOR_MAP_DATA_TYPE_BFLOAT16, rank, const_cast<void*>(ptr), dims, strides, box, es, CU_TENSOR_MAP_INTERLEAVE_NONE, sw,
              CU_TENSOR_MAP_L2_PROMOTION_L2_128B, CU_TENSOR_MAP_FLOAT_OOB_FILL_NONE) == CUDA_SUCCESS;
}
}

extern "C" void kernel_launch(void* const* d_in, const int* in_sizes, int n_in, void* d_out, int out_size) {
    (void)in_sizes; (void)n_in; (void)out_size;
    const __nv_bfloat16* x = (const __nv_bfloat16*)d_in[0];
    const __nv_bfloat16* wqkv = (const __nv_bfloat16*)d_in[1];
    const __nv_bfloat16* wo = (const __nv_bfloat16*)d_in[2];
    const __nv_bfloat16* w1 = (const __nv_bfloat16*)d_in[4];
    const __nv_bfloat16* w3 = (const __nv_bfloat16*)d_in[5];
    const __nv_bfloat16* w2 = (const __nv_bfloat16*)d_in[6];

    static EncodeFn fn = nullptr;
    static void* act = nullptr;
    if (!fn) {
        void* p = nullptr;
        cudaDriverEntryPointQueryResult st;
        cudaGetDriverEntryPoint("cuTensorMapEncodeTiled", &p, cudaEnableDefault, &st);
        fn = (EncodeFn)p;
        cudaFuncSetAttribute(fused_block_kernel, cudaFuncAttributeMaxDynamicSharedMemorySize, SM_TOTAL);
        cudaGetSymbolAddress(&act, g_act);
    }
    Maps maps;
    {
        const cuuint64_t d[3] = {640, 1024, 2}, s[2] = {2560, 1280};
        const cuuint32_t b[3] = {64, 64, 2};
        encode(fn, &maps.x, x, 3, d, s, b, CU_TENSOR_MAP_SWIZZLE_128B);
    }
    {
        const cuuint64_t d[3] = {640, 640, 3}, s[2] = {3840, 1280};
        const cuuint32_t b[3] = {64, 16, 3}, br[3] = {16, 16, 3};
        encode(fn, &maps.wq, wqkv, 3, d, s, b, CU_TENSOR_MAP_SWIZZLE_128B);
        encode(fn, &maps.wqr, wqkv, 3, d, s, br, CU_TENSOR_MAP_SWIZZLE_32B);
    }
    {
        const cuuint64_t d[2] = {1536, 640}, s[1] = {3072};
        const cuuint32_t b[2] = {64, 64};
        encode(fn, &maps.w1, w1, 2, d, s, b, CU_TENSOR_MAP_SWIZZLE_128B);
        encode(fn, &maps.w3, w3, 2, d, s, b, CU_TENSOR_MAP_SWIZZLE_128B);
    }
    {
        const cuuint64_t d[2] = {(cuuint64_t)kActLd, (cuuint64_t)kS}, s[1] = {(cuuint64_t)kActLd * 2};
        const cuuint32_t b[2] = {64, 128};
        encode(fn, &maps.act, act, 2, d, s, b, CU_TENSOR_MAP_SWIZZLE_128B);
    }
    {
        const cuuint64_t do3[3] = {640, 640, 2}, d23[3] = {640, 1536, 2}, s3[2] = {1280, 128};
        const cuuint32_t b3[3] = {64, 32, 2};
        encode(fn, &maps.wo2, wo, 3, do3, s3, b3, CU_TENSOR_MAP_SWIZZLE_128B);
        encode(fn, &maps.w22, w2, 3, d23, s3, b3, CU_TENSOR_MAP_SWIZZLE_128B);
        const cuuint64_t do2[2] = {640, 640}, d22[2] = {640, 1536}, s2[1] = {1280};
        const cuuint32_t b2[2] = {32, 32};
        encode(fn, &maps.wo1, wo, 2, do2, s2, b2, CU_TENSOR_MAP_SWIZZLE_128B);
        encode(fn, &maps.w21, w2, 2, d22, s2, b2, CU_TENSOR_MAP_SWIZZLE_128B);
    }
    fused_block_kernel<<<128, 384, SM_TOTAL>>>(maps, x, wqkv, w1, w3, wo, w2, (__nv_bfloat16*)d_out);
}
```

```cpp
#include <cuda_runtime.h>
#include <cuda_bf16.h>
#include <cuda.h>
#include <stdint.h>

namespace {

constexpr int kS = 2048, kD = 640, kF = 1536;
constexpr int kActLd = kD + kF;

constexpr uint32_t SM_X = 0;
constexpr uint32_t SM_RING = 163840;
constexpr uint32_t SM_MISC = 229376;
constexpr uint32_t SM_BAR = SM_MISC;
constexpr uint32_t SM_CS = SM_MISC + 576;
constexpr uint32_t SM_ST = SM_CS + 960;
constexpr uint32_t SM_NM = SM_ST + 1024;
constexpr uint32_t SM_TOTAL = 232448;
constexpr uint32_t G_STAGE = 40960;
static_assert(SM_NM + 512 <= SM_TOTAL, "smem map");

constexpr int B_XFULL = 0;
constexpr int B_RFULL = 10;
constexpr int B_REMPTYQ = 14;
constexpr int B_REMPTYF = 18;
constexpr int B_GFULL = 22;
constexpr int B_GEMPTY = 27;
constexpr int B_CS = 32;
constexpr int B_ST = 33;
constexpr int B_HALOW = 34;
constexpr int B_HALOR = 35;
constexpr int B_WDONE = 37;
constexpr int B_FLAG = 41;
constexpr int B_XFREE = 45;
constexpr int B_XN = 55;
constexpr int B_COUNT = 65;

constexpr int NT_G = 17;
constexpr int PF_DIST = 6;
#define SILU_TANH 1

__device__ __align__(1024) __nv_bfloat16 g_act[kS * kActLd];
__device__ __align__(128) unsigned long long g_cs[8 * 256];
__device__ __align__(128) unsigned long long g_stats[kS * 2];
__device__ __align__(128) uint4 g_halo[16 * 8 * 2 * 4 * 5 * 32];
__device__ __align__(128) unsigned g_cntO[16 * 32];
__device__ __align__(128) unsigned g_cntH[16 * 3 * 32];
__device__ __align__(128) unsigned g_flagHalo[16 * 8 * 32];
#define TRACE(slot) do { } while (0)
#define TRACEG(slot) do { } while (0)

struct Maps {
    CUtensorMap x, wq, wqr, w1, w3, act, wo2, wo1, w22, w21;
};

__device__ __forceinline__ long long gtime() { long long t; asm volatile("mov.u64 %0, %%globaltimer;" : "=l"(t)); return t; }
__device__ __forceinline__ uint32_t smem_u32(const void* p) { return (uint32_t)__cvta_generic_to_shared(p); }
__device__ __forceinline__ uint32_t launder(uint32_t x) { uint32_t y; asm volatile("mov.u32 %0, %1;" : "=r"(y) : "r"(x)); return y; }
__device__ __forceinline__ bool elect_one() {
    uint32_t p;
    asm volatile("{\n.reg .pred P;\nelect.sync _|P, 0xffffffff;\nselp.u32 %0,1,0,P;\n}" : "=r"(p));
    return p;
}
__device__ __forceinline__ void mbar_init(uint32_t bar, uint32_t cnt) { asm volatile("mbarrier.init.shared::cta.b64 [%0], %1;" ::"r"(bar), "r"(cnt)); }
__device__ __forceinline__ void mbar_expect_tx(uint32_t bar, uint32_t bytes) {
    asm volatile("mbarrier.arrive.expect_tx.shared::cta.b64 _, [%0], %1;" ::"r"(bar), "r"(bytes) : "memory");
}
__device__ __forceinline__ void mbar_arrive(uint32_t bar) { asm volatile("mbarrier.arrive.shared::cta.b64 _, [%0];" ::"r"(bar) : "memory"); }
__device__ __forceinline__ void mbar_arrive_cluster(uint32_t bar_cluster_addr) {
    asm volatile("mbarrier.arrive.shared::cluster.b64 _, [%0];" ::"r"(bar_cluster_addr) : "memory");
}
__device__ __forceinline__ uint32_t mapa(uint32_t addr, uint32_t cta) {
    uint32_t r; asm("mapa.shared::cluster.u32 %0, %1, %2;" : "=r"(r) : "r"(addr), "r"(cta)); return r;
}
__device__ __forceinline__ bool mbar_try(uint32_t bar, uint32_t parity) {
    uint32_t ok;
    asm volatile("{\n.reg .pred p;\nmbarrier.try_wait.parity.shared::cta.b64 p, [%1], %2;\nselp.u32 %0,1,0,p;\n}"
                 : "=r"(ok) : "r"(bar), "r"(parity) : "memory");
    return ok;
}
__device__ __forceinline__ void mbar_wait(uint32_t bar, uint32_t parity) {
    int it = 0;
#pragma unroll 1
    while (!mbar_try(bar, parity)) { if (++it > (1 << 17)) break; }
}
__device__ __forceinline__ void tma2(uint32_t dst, const CUtensorMap* m, int c0, int c1, uint32_t bar) {
    asm volatile("cp.async.bulk.tensor.2d.shared::cluster.global.mbarrier::complete_tx::bytes [%0], [%1, {%3, %4}], [%2];"
                 ::"r"(dst), "l"(m), "r"(bar), "r"(c0), "r"(c1) : "memory");
}
__device__ __forceinline__ void tma3(uint32_t dst, const CUtensorMap* m, int c0, int c1, int c2, uint32_t bar) {
    asm volatile("cp.async.bulk.tensor.3d.shared::cluster.global.mbarrier::complete_tx::bytes [%0], [%1, {%3, %4, %5}], [%2];"
                 ::"r"(dst), "l"(m), "r"(bar), "r"(c0), "r"(c1), "r"(c2) : "memory");
}
__device__ __forceinline__ void tma2_mc(uint32_t dst, const CUtensorMap* m, int c0, int c1, uint32_t bar) {
    asm volatile("cp.async.bulk.tensor.2d.shared::cluster.global.mbarrier::complete_tx::bytes.multicast::cluster [%0], [%1, {%3, %4}], [%2], %5;"
                 ::"r"(dst), "l"(m), "r"(bar), "r"(c0), "r"(c1), "h"((uint16_t)3) : "memory");
}
__device__ __forceinline__ void tma3_mc(uint32_t dst, const CUtensorMap* m, int c0, int c1, int c2, uint32_t bar) {
    asm volatile("cp.async.bulk.tensor.3d.shared::cluster.global.mbarrier::complete_tx::bytes.multicast::cluster [%0], [%1, {%3, %4, %5}], [%2], %6;"
                 ::"r"(dst), "l"(m), "r"(bar), "r"(c0), "r"(c1), "r"(c2), "h"((uint16_t)3) : "memory");
}
__device__ __forceinline__ void tma4_mc(uint32_t dst, const CUtensorMap* m, int c0, int c2, uint32_t bar) {
    asm volatile("cp.async.bulk.tensor.4d.shared::cluster.global.mbarrier::complete_tx::bytes.multicast::cluster [%0], [%1, {%3, %5, %4, %5}], [%2], %6;"
                 ::"r"(dst), "l"(m), "r"(bar), "r"(c0), "r"(c2), "r"(0), "h"((uint16_t)3) : "memory");
}
__device__ __forceinline__ void tma5_mc(uint32_t dst, const CUtensorMap* m, int c0, int c2, uint32_t bar) {
    asm volatile("cp.async.bulk.tensor.5d.shared::cluster.global.mbarrier::complete_tx::bytes.multicast::cluster [%0], [%1, {%3, %5, %4, %5, %5}], [%2], %6;"
                 ::"r"(dst), "l"(m), "r"(bar), "r"(c0), "r"(c2), "r"(0), "h"((uint16_t)3) : "memory");
}
__device__ __forceinline__ void bulk_g2s(uint32_t dst, const void* src, uint32_t bytes, uint32_t bar) {
    asm volatile("cp.async.bulk.shared::cluster.global.mbarrier::complete_tx::bytes [%0], [%1], %2, [%3];"
                 ::"r"(dst), "l"(src), "r"(bytes), "r"(bar) : "memory");
}
__device__ __forceinline__ uint4 lds128(uint32_t a) {
    uint4 v; asm volatile("ld.shared.v4.u32 {%0,%1,%2,%3}, [%4];" : "=r"(v.x), "=r"(v.y), "=r"(v.z), "=r"(v.w) : "r"(a) : "memory"); return v;
}
__device__ __forceinline__ void sts128(uint32_t a, uint4 v) {
    asm volatile("st.shared.v4.u32 [%0], {%1,%2,%3,%4};" ::"r"(a), "r"(v.x), "r"(v.y), "r"(v.z), "r"(v.w) : "memory");
}
__device__ __forceinline__ void prefetch_map(const CUtensorMap* m) { asm volatile("prefetch.tensormap [%0];" ::"l"(m) : "memory"); }
__device__ __forceinline__ void prefetch_l2(const void* p, uint32_t bytes) {
    asm volatile("cp.async.bulk.prefetch.L2.global [%0], %1;" ::"l"(p), "r"(bytes) : "memory");
}
__device__ __forceinline__ void wg_fence() { asm volatile("wgmma.fence.sync.aligned;" ::: "memory"); }
__device__ __forceinline__ void wg_commit() { asm volatile("wgmma.commit_group.sync.aligned;" ::: "memory"); }
template <int N> __device__ __forceinline__ void wg_wait() { asm volatile("wgmma.wait_group.sync.aligned %0;" ::"n"(N) : "memory"); }
__device__ __forceinline__ unsigned ld_acquire(const unsigned* p) {
    unsigned v; asm volatile("ld.acquire.gpu.global.u32 %0, [%1];" : "=r"(v) : "l"(p) : "memory"); return v;
}
__device__ __forceinline__ void fence_gpu() { asm volatile("fence.acq_rel.gpu;" ::: "memory"); }
__device__ __forceinline__ void fence_async_global() { asm volatile("fence.proxy.async.global;" ::: "memory"); }
__device__ __forceinline__ void red_add(unsigned* p, unsigned v) { asm volatile("red.relaxed.gpu.global.add.u32 [%0], %1;" ::"l"(p), "r"(v) : "memory"); }
__device__ __forceinline__ void st_relaxed(unsigned* p, unsigned v) { asm volatile("st.relaxed.gpu.global.u32 [%0], %1;" ::"l"(p), "r"(v) : "memory"); }
__device__ __forceinline__ unsigned ld_relaxed(const unsigned* p) {
    unsigned v; asm volatile("ld.relaxed.gpu.global.u32 %0, [%1];" : "=r"(v) : "l"(p) : "memory"); return v;
}
__device__ __forceinline__ unsigned long long tagged(unsigned tag, float v) { return ((unsigned long long)tag << 32) | __float_as_uint(v); }
__device__ __forceinline__ void st_tag2(unsigned long long* p, unsigned long long a, unsigned long long b) {
    asm volatile("st.relaxed.gpu.global.v2.b64 [%0], {%1, %2};" ::"l"(p), "l"(a), "l"(b) : "memory");
}
__device__ __forceinline__ void st_tag(unsigned long long* p, unsigned long long a) {
    asm volatile("st.relaxed.gpu.global.b64 [%0], %1;" ::"l"(p), "l"(a) : "memory");
}
__device__ __forceinline__ void ld_tag2(const unsigned long long* p, unsigned long long& a, unsigned long long& b) {
    asm volatile("ld.relaxed.gpu.global.v2.b64 {%0, %1}, [%2];" : "=l"(a), "=l"(b) : "l"(p) : "memory");
}
__device__ __forceinline__ void poll_ge(const unsigned* p, unsigned target) {
    int it = 0;
#pragma unroll 1
    while ((int)(ld_acquire(p) - target) < 0) { if (++it > (1 << 16)) break; }
}
template <int ID, int N> __device__ __forceinline__ void bar_sync() { asm volatile("bar.sync %0, %1;" ::"n"(ID), "n"(N) : "memory"); }
__device__ __forceinline__ float ex2(float x) { float y; asm("ex2.approx.ftz.f32 %0, %1;" : "=f"(y) : "f"(x)); return y; }
__device__ __forceinline__ float rcp(float x) { float y; asm("rcp.approx.ftz.f32 %0, %1;" : "=f"(y) : "f"(x)); return y; }
__device__ __forceinline__ float tanh_fast(float x) { float y; asm("tanh.approx.f32 %0, %1;" : "=f"(y) : "f"(x)); return y; }
__device__ __forceinline__ uint32_t badd2(uint32_t a, uint32_t b) { uint32_t d; asm("add.rn.bf16x2 %0, %1, %2;" : "=r"(d) : "r"(a), "r"(b)); return d; }
__device__ __forceinline__ uint32_t lds32(uint32_t a) { uint32_t v; asm volatile("ld.shared.u32 %0, [%1];" : "=r"(v) : "r"(a) : "memory"); return v; }
__device__ __forceinline__ uint32_t pack2(float lo, float hi) {
    uint32_t r; asm("cvt.rn.bf16x2.f32 %0, %1, %2;" : "=r"(r) : "f"(hi), "f"(lo)); return r;
}
__device__ __forceinline__ float bf_lo(uint32_t v) { return __uint_as_float(v << 16); }
__device__ __forceinline__ float bf_hi(uint32_t v) { return __uint_as_float(v & 0xffff0000u); }
__device__ __forceinline__ float2 lds64(uint32_t a) { float2 v; asm volatile("ld.shared.v2.f32 {%0,%1}, [%2];" : "=f"(v.x), "=f"(v.y) : "r"(a)); return v; }
__device__ __forceinline__ void mma16(float (&c)[4], uint32_t a0, uint32_t a1, uint32_t a2, uint32_t a3, uint32_t b0, uint32_t b1) {
    asm("mma.sync.aligned.m16n8k16.row.col.f32.bf16.bf16.f32 {%0,%1,%2,%3}, {%4,%5,%6,%7}, {%8,%9}, {%0,%1,%2,%3};"
        : "+f"(c[0]), "+f"(c[1]), "+f"(c[2]), "+f"(c[3]) : "r"(a0), "r"(a1), "r"(a2), "r"(a3), "r"(b0), "r"(b1));
}
__device__ __forceinline__ void mma8(float (&c)[4], uint32_t a0, uint32_t a1, uint32_t b0) {
    asm("mma.sync.aligned.m16n8k8.row.col.f32.bf16.bf16.f32 {%0,%1,%2,%3}, {%4,%5}, {%6}, {%0,%1,%2,%3};"
        : "+f"(c[0]), "+f"(c[1]), "+f"(c[2]), "+f"(c[3]) : "r"(a0), "r"(a1), "r"(b0));
}
__device__ __forceinline__ uint32_t movm(uint32_t a) {
    uint32_t d; asm("movmatrix.sync.aligned.m8n8.trans.b16 %0, %1;" : "=r"(d) : "r"(a)); return d;
}

__device__ __forceinline__ void wgmma_n48(float (&d)[24], uint32_t alo, uint32_t ahi, uint32_t blo, uint32_t bhi, int sd) {
    asm volatile("{\n.reg .pred p;\n.reg .b64 da, db;\nsetp.ne.b32 p, %28, 0;\nmov.b64 da, {%24,%25};\nmov.b64 db, {%26,%27};\n"
        "wgmma.mma_async.sync.aligned.m64n48k16.f32.bf16.bf16 {"
        "%0,%1,%2,%3,%4,%5,%6,%7,%8,%9,%10,%11,%12,%13,%14,%15,"
        "%16,%17,%18,%19,%20,%21,%22,%23"
        "}, da, db, p, 1, 1, 0, 1;\n}\n"
        : "+f"(d[0]), "+f"(d[1]), "+f"(d[2]), "+f"(d[3]), "+f"(d[4]), "+f"(d[5]), "+f"(d[6]), "+f"(d[7]),
          "+f"(d[8]), "+f"(d[9]), "+f"(d[10]), "+f"(d[11]), "+f"(d[12]), "+f"(d[13]), "+f"(d[14]), "+f"(d[15]),
          "+f"(d[16]), "+f"(d[17]), "+f"(d[18]), "+f"(d[19]), "+f"(d[20]), "+f"(d[21]), "+f"(d[22]), "+f"(d[23])
        : "r"(alo), "r"(ahi), "r"(blo), "r"(bhi), "r"(sd));
}
__device__ __forceinline__ void wgmma_n128(float (&d)[64], uint32_t alo, uint32_t ahi, uint32_t blo, uint32_t bhi, int sd) {
    asm volatile("{\n.reg .pred p;\n.reg .b64 da, db;\nsetp.ne.b32 p, %68, 0;\nmov.b64 da, {%64,%65};\nmov.b64 db, {%66,%67};\n"
        "wgmma.mma_async.sync.aligned.m64n128k16.f32.bf16.bf16 {"
        "%0,%1,%2,%3,%4,%5,%6,%7,%8,%9,%10,%11,%12,%13,%14,%15,"
        "%16,%17,%18,%19,%20,%21,%22,%23,%24,%25,%26,%27,%28,%29,%30,%31,"
        "%32,%33,%34,%35,%36,%37,%38,%39,%40,%41,%42,%43,%44,%45,%46,%47,"
        "%48,%49,%50,%51,%52,%53,%54,%55,%56,%57,%58,%59,%60,%61,%62,%63"
        "}, da, db, p, 1, 1, 0, 1;\n}\n"
        : "+f"(d[0]), "+f"(d[1]), "+f"(d[2]), "+f"(d[3]), "+f"(d[4]), "+f"(d[5]), "+f"(d[6]), "+f"(d[7]),
          "+f"(d[8]), "+f"(d[9]), "+f"(d[10]), "+f"(d[11]), "+f"(d[12]), "+f"(d[13]), "+f"(d[14]), "+f"(d[15]),
          "+f"(d[16]), "+f"(d[17]), "+f"(d[18]), "+f"(d[19]), "+f"(d[20]), "+f"(d[21]), "+f"(d[22]), "+f"(d[23]),
          "+f"(d[24]), "+f"(d[25]), "+f"(d[26]), "+f"(d[27]), "+f"(d[28]), "+f"(d[29]), "+f"(d[30]), "+f"(d[31]),
          "+f"(d[32]), "+f"(d[33]), "+f"(d[34]), "+f"(d[35]), "+f"(d[36]), "+f"(d[37]), "+f"(d[38]), "+f"(d[39]),
          "+f"(d[40]), "+f"(d[41]), "+f"(d[42]), "+f"(d[43]), "+f"(d[44]), "+f"(d[45]), "+f"(d[46]), "+f"(d[47]),
          "+f"(d[48]), "+f"(d[49]), "+f"(d[50]), "+f"(d[51]), "+f"(d[52]), "+f"(d[53]), "+f"(d[54]), "+f"(d[55]),
          "+f"(d[56]), "+f"(d[57]), "+f"(d[58]), "+f"(d[59]), "+f"(d[60]), "+f"(d[61]), "+f"(d[62]), "+f"(d[63])
        : "r"(alo), "r"(ahi), "r"(blo), "r"(bhi), "r"(sd));
}
__device__ __forceinline__ void wgmma_n160(float (&d)[80], uint32_t alo, uint32_t ahi, uint32_t blo, uint32_t bhi, int sd) {
    asm volatile("{\n.reg .pred p;\n.reg .b64 da, db;\nsetp.ne.b32 p, %84, 0;\nmov.b64 da, {%80,%81};\nmov.b64 db, {%82,%83};\n"
        "wgmma.mma_async.sync.aligned.m64n160k16.f32.bf16.bf16 {"
        "%0,%1,%2,%3,%4,%5,%6,%7,%8,%9,%10,%11,%12,%13,%14,%15,"
        "%16,%17,%18,%19,%20,%21,%22,%23,%24,%25,%26,%27,%28,%29,%30,%31,"
        "%32,%33,%34,%35,%36,%37,%38,%39,%40,%41,%42,%43,%44,%45,%46,%47,"
        "%48,%49,%50,%51,%52,%53,%54,%55,%56,%57,%58,%59,%60,%61,%62,%63,"
        "%64,%65,%66,%67,%68,%69,%70,%71,%72,%73,%74,%75,%76,%77,%78,%79"
        "}, da, db, p, 1, 1, 0, 1;\n}\n"
        : "+f"(d[0]), "+f"(d[1]), "+f"(d[2]), "+f"(d[3]), "+f"(d[4]), "+f"(d[5]), "+f"(d[6]), "+f"(d[7]),
          "+f"(d[8]), "+f"(d[9]), "+f"(d[10]), "+f"(d[11]), "+f"(d[12]), "+f"(d[13]), "+f"(d[14]), "+f"(d[15]),
          "+f"(d[16]), "+f"(d[17]), "+f"(d[18]), "+f"(d[19]), "+f"(d[20]), "+f"(d[21]), "+f"(d[22]), "+f"(d[23]),
          "+f"(d[24]), "+f"(d[25]), "+f"(d[26]), "+f"(d[27]), "+f"(d[28]), "+f"(d[29]), "+f"(d[30]), "+f"(d[31]),
          "+f"(d[32]), "+f"(d[33]), "+f"(d[34]), "+f"(d[35]), "+f"(d[36]), "+f"(d[37]), "+f"(d[38]), "+f"(d[39]),
          "+f"(d[40]), "+f"(d[41]), "+f"(d[42]), "+f"(d[43]), "+f"(d[44]), "+f"(d[45]), "+f"(d[46]), "+f"(d[47]),
          "+f"(d[48]), "+f"(d[49]), "+f"(d[50]), "+f"(d[51]), "+f"(d[52]), "+f"(d[53]), "+f"(d[54]), "+f"(d[55]),
          "+f"(d[56]), "+f"(d[57]), "+f"(d[58]), "+f"(d[59]), "+f"(d[60]), "+f"(d[61]), "+f"(d[62]), "+f"(d[63]),
          "+f"(d[64]), "+f"(d[65]), "+f"(d[66]), "+f"(d[67]), "+f"(d[68]), "+f"(d[69]), "+f"(d[70]), "+f"(d[71]),
          "+f"(d[72]), "+f"(d[73]), "+f"(d[74]), "+f"(d[75]), "+f"(d[76]), "+f"(d[77]), "+f"(d[78]), "+f"(d[79])
        : "r"(alo), "r"(ahi), "r"(blo), "r"(bhi), "r"(sd));
}
__device__ __forceinline__ void wgmma_n192(float (&d)[96], uint32_t alo, uint32_t ahi, uint32_t blo, uint32_t bhi, int sd) {
    asm volatile("{\n.reg .pred p;\n.reg .b64 da, db;\nsetp.ne.b32 p, %100, 0;\nmov.b64 da, {%96,%97};\nmov.b64 db, {%98,%99};\n"
        "wgmma.mma_async.sync.aligned.m64n192k16.f32.bf16.bf16 {"
        "%0,%1,%2,%3,%4,%5,%6,%7,%8,%9,%10,%11,%12,%13,%14,%15,"
        "%16,%17,%18,%19,%20,%21,%22,%23,%24,%25,%26,%27,%28,%29,%30,%31,"
        "%32,%33,%34,%35,%36,%37,%38,%39,%40,%41,%42,%43,%44,%45,%46,%47,"
        "%48,%49,%50,%51,%52,%53,%54,%55,%56,%57,%58,%59,%60,%61,%62,%63,"
        "%64,%65,%66,%67,%68,%69,%70,%71,%72,%73,%74,%75,%76,%77,%78,%79,"
        "%80,%81,%82,%83,%84,%85,%86,%87,%88,%89,%90,%91,%92,%93,%94,%95"
        "}, da, db, p, 1, 1, 0, 1;\n}\n"
        : "+f"(d[0]), "+f"(d[1]), "+f"(d[2]), "+f"(d[3]), "+f"(d[4]), "+f"(d[5]), "+f"(d[6]), "+f"(d[7]),
          "+f"(d[8]), "+f"(d[9]), "+f"(d[10]), "+f"(d[11]), "+f"(d[12]), "+f"(d[13]), "+f"(d[14]), "+f"(d[15]),
          "+f"(d[16]), "+f"(d[17]), "+f"(d[18]), "+f"(d[19]), "+f"(d[20]), "+f"(d[21]), "+f"(d[22]), "+f"(d[23]),
          "+f"(d[24]), "+f"(d[25]), "+f"(d[26]), "+f"(d[27]), "+f"(d[28]), "+f"(d[29]), "+f"(d[30]), "+f"(d[31]),
          "+f"(d[32]), "+f"(d[33]), "+f"(d[34]), "+f"(d[35]), "+f"(d[36]), "+f"(d[37]), "+f"(d[38]), "+f"(d[39]),
          "+f"(d[40]), "+f"(d[41]), "+f"(d[42]), "+f"(d[43]), "+f"(d[44]), "+f"(d[45]), "+f"(d[46]), "+f"(d[47]),
          "+f"(d[48]), "+f"(d[49]), "+f"(d[50]), "+f"(d[51]), "+f"(d[52]), "+f"(d[53]), "+f"(d[54]), "+f"(d[55]),
          "+f"(d[56]), "+f"(d[57]), "+f"(d[58]), "+f"(d[59]), "+f"(d[60]), "+f"(d[61]), "+f"(d[62]), "+f"(d[63]),
          "+f"(d[64]), "+f"(d[65]), "+f"(d[66]), "+f"(d[67]), "+f"(d[68]), "+f"(d[69]), "+f"(d[70]), "+f"(d[71]),
          "+f"(d[72]), "+f"(d[73]), "+f"(d[74]), "+f"(d[75]), "+f"(d[76]), "+f"(d[77]), "+f"(d[78]), "+f"(d[79]),
          "+f"(d[80]), "+f"(d[81]), "+f"(d[82]), "+f"(d[83]), "+f"(d[84]), "+f"(d[85]), "+f"(d[86]), "+f"(d[87]),
          "+f"(d[88]), "+f"(d[89]), "+f"(d[90]), "+f"(d[91]), "+f"(d[92]), "+f"(d[93]), "+f"(d[94]), "+f"(d[95])
        : "r"(alo), "r"(ahi), "r"(blo), "r"(bhi), "r"(sd));
}

constexpr uint32_t HI_128 = 0x40000040u;
constexpr uint32_t HI_32 = 0xC0000010u;
__device__ __forceinline__ constexpr uint32_t lbo(uint32_t bytes) { return (bytes >> 4) << 16; }

struct Ctx {
    uint32_t sb;
    uint32_t bar;
    uint32_t rbar;
    uint32_t a_lo;
    uint32_t b_lo;
    int lane, q, g, w, par;
    float n0, n1, r0, r1;
    float ga0, ga1, gb0, gb1;
};

__device__ __forceinline__ void arrive_both(const Ctx& c, int bar_idx) {
    if (c.lane < 2) mbar_arrive_cluster(c.rbar + bar_idx * 8);
}
__device__ __forceinline__ void arrive_local(const Ctx& c, int bar_idx) {
    __syncwarp();
    if (c.lane == 0) mbar_arrive(c.bar + bar_idx * 8);
}

__device__ __forceinline__ void red_pair(__nv_bfloat16* rowp  , int q, uint32_t a, uint32_t b) {
    const bool odd = q & 1;
    const uint32_t send = odd ? a : b;
    const uint32_t recv = __shfl_xor_sync(0xffffffffu, send, 1);
    const uint32_t v0 = odd ? recv : a, v1 = odd ? b : recv;
    __nv_bfloat16* p = rowp + (odd ? 8 + 2 * (q - 1) : 2 * q);
    asm volatile("red.relaxed.gpu.global.add.noftz.v2.bf16x2 [%0], {%1, %2};" ::"l"(p), "r"(v0), "r"(v1) : "memory");
}
__device__ __forceinline__ void stg128(__nv_bfloat16* p, uint32_t a, uint32_t b, uint32_t c, uint32_t d) {
    *reinterpret_cast<uint4*>(p) = make_uint4(a, b, c, d);
}

__device__ __forceinline__ void ln_pack(const Ctx& c, const float* a, int col, uint32_t& lo, uint32_t& hi) {
    float2 cs = lds64(c.sb + SM_CS + (col + 2 * c.q) * 4);
    lo = pack2(fmaf(a[0], c.r0, c.n0 * cs.x), fmaf(a[1], c.r0, c.n0 * cs.y));
    hi = pack2(fmaf(a[2], c.r1, c.n1 * cs.x), fmaf(a[3], c.r1, c.n1 * cs.y));
}
template <int PART, int G0, int G1>
__device__ __forceinline__ void qkv_pack(const Ctx& c, const float (&a1)[96], const float (&a2)[24], uint32_t (&dst)[20]) {
#pragma unroll
    for (int G = G0; G < G1; G++) {
        if (G < 8) ln_pack(c, &a1[PART * 32 + G * 4], PART * 64 + G * 8, dst[2 * G], dst[2 * G + 1]);
        else ln_pack(c, &a2[PART * 8 + (G - 8) * 4], 192 + PART * 16 + (G - 8) * 8, dst[2 * G], dst[2 * G + 1]);
    }
}

template <int H>
__device__ __forceinline__ void attn_logits(const Ctx& c, bool first, const uint32_t (&qp)[20], const uint32_t (&kp)[20],
                                            const uint32_t (&hk)[10], float (&s)[4]) {
    constexpr int GA = (H == 0) ? 0 : (H == 1) ? 3 : (H == 2) ? 5 : 8;
    constexpr int GS = (H < 2) ? 2 : 7;
    const bool mine = (H & 1) ? (c.q >= 2) : (c.q < 2);
    const uint32_t qs0 = mine ? qp[2 * GS] : 0u, qs1 = mine ? qp[2 * GS + 1] : 0u;
    float sP[4] = {0.f, 0.f, 0.f, 0.f}, sL[4] = {0.f, 0.f, 0.f, 0.f}, sU[4] = {0.f, 0.f, 0.f, 0.f};
    mma16(sP, qp[2 * GA], qp[2 * GA + 1], qp[2 * GA + 2], qp[2 * GA + 3], hk[GA], hk[GA + 1]);
    mma16(sL, qp[2 * GA], qp[2 * GA + 1], qp[2 * GA + 2], qp[2 * GA + 3], kp[2 * GA], kp[2 * GA + 2]);
    mma16(sU, qp[2 * GA], qp[2 * GA + 1], qp[2 * GA + 2], qp[2 * GA + 3], kp[2 * GA + 1], kp[2 * GA + 3]);
    mma8(sP, qs0, qs1, hk[GS]);
    mma8(sL, qs0, qs1, kp[2 * GS]);
    mma8(sU, qs0, qs1, kp[2 * GS + 1]);
    const bool gt0 = 2 * c.q > c.g, gt1 = 2 * c.q + 1 > c.g;
    const float ninf = __int_as_float(0xff800000);
    s[0] = gt0 ? (first ? ninf : sP[0]) : sL[0];
    s[1] = gt1 ? (first ? ninf : sP[1]) : sL[1];
    s[2] = gt0 ? sL[2] : sU[2];
    s[3] = gt1 ? sL[3] : sU[3];
}
constexpr float kScale = 0.22360679774997896f * 1.4426950408889634f;
__device__ __forceinline__ void attn_max(const float (&s)[4][4], float (&m)[4][2]) {
#pragma unroll
    for (int h = 0; h < 4; h++) { m[h][0] = fmaxf(s[h][0], s[h][1]); m[h][1] = fmaxf(s[h][2], s[h][3]); }
#pragma unroll
    for (int o = 1; o < 4; o <<= 1) {
#pragma unroll
        for (int h = 0; h < 4; h++) {
            m[h][0] = fmaxf(m[h][0], __shfl_xor_sync(0xffffffffu, m[h][0], o));
            m[h][1] = fmaxf(m[h][1], __shfl_xor_sync(0xffffffffu, m[h][1], o));
        }
    }
}
__device__ __forceinline__ void attn_exp(float (&s)[4][4], float (&m)[4][2]) {
#pragma unroll
    for (int h = 0; h < 4; h++) {
        const float m0 = m[h][0] * -kScale, m1 = m[h][1] * -kScale;
        s[h][0] = ex2(fmaf(s[h][0], kScale, m0)); s[h][1] = ex2(fmaf(s[h][1], kScale, m0));
        s[h][2] = ex2(fmaf(s[h][2], kScale, m1)); s[h][3] = ex2(fmaf(s[h][3], kScale, m1));
        m[h][0] = s[h][0] + s[h][1]; m[h][1] = s[h][2] + s[h][3];
    }
}
__device__ __forceinline__ void attn_sum(float (&m)[4][2]) {
#pragma unroll
    for (int o = 1; o < 4; o <<= 1) {
#pragma unroll
        for (int h = 0; h < 4; h++) {
            m[h][0] += __shfl_xor_sync(0xffffffffu, m[h][0], o);
            m[h][1] += __shfl_xor_sync(0xffffffffu, m[h][1], o);
        }
    }
#pragma unroll
    for (int h = 0; h < 4; h++) { m[h][0] = rcp(m[h][0]); m[h][1] = rcp(m[h][1]); }
}
__device__ __forceinline__ void attn_probs(const Ctx& c, const float (&s)[4][4], const float (&m)[4][2], uint32_t (&p)[4][4]) {
    const uint32_t mk = ((2 * c.q > c.g) ? 0x0000ffffu : 0u) | ((2 * c.q + 1 > c.g) ? 0xffff0000u : 0u);
#pragma unroll
    for (int h = 0; h < 4; h++) {
        const uint32_t lo = pack2(s[h][0] * m[h][0], s[h][1] * m[h][0]), hi = pack2(s[h][2] * m[h][1], s[h][3] * m[h][1]);
        p[h][0] = lo & mk; p[h][1] = lo & ~mk; p[h][2] = hi & mk; p[h][3] = hi & ~mk;
    }
}
template <int H>
__device__ __forceinline__ void attn_pv(const Ctx& c, const uint32_t (&p)[4], const uint32_t (&vp)[20], const uint32_t (&hv)[10], uint32_t (&op)[20]) {
    constexpr int GA = (H == 0) ? 0 : (H == 1) ? 3 : (H == 2) ? 5 : 8;
    constexpr int GS = (H < 2) ? 2 : 7;
    const bool mine = (H & 1) ? (c.q >= 2) : (c.q < 2);
#pragma unroll
    for (int t = 0; t < 3; t++) {
        const int G = (t < 2) ? GA + t : GS;
        float o[4] = {0.f, 0.f, 0.f, 0.f};
        mma16(o, p[0], 0u, p[1], p[2], movm(hv[G]), movm(vp[2 * G]));
        mma8(o, 0u, p[3], movm(vp[2 * G + 1]));
        const uint32_t lo = pack2(o[0], o[1]), hi = pack2(o[2], o[3]);
        if (t < 2 || (H & 1) == 0) { op[2 * G] = lo; op[2 * G + 1] = hi; }
        else { op[2 * G] = mine ? lo : op[2 * G]; op[2 * G + 1] = mine ? hi : op[2 * G + 1]; }
    }
}

__device__ __forceinline__ void swiglu_group(const Ctx& c, const float (&acc)[64], int G, uint32_t& lo, uint32_t& hi) {
    float h[4];
#pragma unroll
    for (int e = 0; e < 4; e++) {
        const float gate = acc[4 * G + e], up = acc[32 + 4 * G + e];
        const float ga = (e < 2) ? c.ga0 : c.ga1, gb = (e < 2) ? c.gb0 : c.gb1;
        h[e] = (gate * up) * fmaf(tanh_fast(gate * ga), gb, gb);
    }
    lo = pack2(h[0], h[1]);
    hi = pack2(h[2], h[3]);
}
template <int G0, int G1>
__device__ __forceinline__ void swiglu_groups(const Ctx& c, const float (&acc)[64], uint32_t (&hp)[8], __nv_bfloat16* hrow) {
#pragma unroll
    for (int G = G0; G < G1; G++) {
        swiglu_group(c, acc, G, hp[G & 3], hp[4 + (G & 3)]);
        if ((G & 3) == 3) {
            stg128(hrow + 32 * (G >> 2), hp[0], hp[1], hp[2], hp[3]);
            stg128(hrow + 8 * kActLd + 32 * (G >> 2), hp[4], hp[5], hp[6], hp[7]);
        }
    }
}

template <int N>
__device__ __forceinline__ void f_issue(const Ctx& c, float (&acc)[64]) {
    constexpr int S = (N - 20) % 10, SLOT = N & 3;
    if (N < 30) mbar_wait(c.bar + (B_XN + S) * 8, 0);
    mbar_wait(c.bar + (B_RFULL + SLOT) * 8, (N >> 2) & 1);
    if (threadIdx.x < 32) TRACE(64 + N);
    wg_fence();
#pragma unroll
    for (int kk = 0; kk < 4; kk++)
        wgmma_n128(acc, c.a_lo + S * 1024 + kk * 2, HI_128, c.b_lo + lbo(8192) + SLOT * 1024 + kk * 128, HI_128, (S | kk) != 0);
    wg_commit();
    wg_wait<1>();
    if (N - 1 <= 45) arrive_both(c, (N - 1 < 20 ? B_REMPTYQ : B_REMPTYF) + ((N - 1) & 3));
    if (N == 20 && c.lane == 0) mbar_arrive(c.bar + (B_XFREE + 9) * 8);
    if (N == 43) arrive_both(c, B_GEMPTY + 0);
    if (N == 45) arrive_both(c, B_GEMPTY + 1);
    if (N == 48) arrive_both(c, B_GEMPTY + 2);
}

__device__ __forceinline__ void g_issue(const Ctx& c, float (&acc)[80], int slot, int parity, bool first, int t) {
    mbar_wait(c.bar + (B_GFULL + slot) * 8, parity);
    if (threadIdx.x < 32) TRACE(120 + t);
    wg_fence();
    const uint32_t st = ((c.sb & 0x3FFFF) >> 4) + slot * (G_STAGE >> 4);
    const uint32_t alo = st + c.par * 512 + lbo(16), blo = st + 1024 + lbo(4096);
#pragma unroll
    for (int kk = 0; kk < 4; kk++)
        wgmma_n160(acc, alo + kk * 2, HI_128, blo + (kk >> 1) * 768 + (kk & 1) * 128, HI_128, !(first && kk == 0));
    wg_commit();
}

template <int N>
__device__ __forceinline__ void halve(float (&acc)[16], int lane) {
    const bool up = lane & (2 * N);
#pragma unroll
    for (int e = 0; e < N; e++) {
        const float lo = acc[e], hi = acc[e + N];
        const float send = up ? lo : hi, keep = up ? hi : lo;
        acc[e] = keep + __shfl_xor_sync(0xffffffffu, send, 2 * N);
    }
}

__device__ __forceinline__ void prefetch_stage(int m, int b, const __nv_bfloat16* wqkv, const __nv_bfloat16* w1, const __nv_bfloat16* w3) {
    if (m < 20) prefetch_l2(wqkv + (size_t)(32 * m + (b & 31)) * 1920 + (b >> 5) * 480, 960);
    else if (m < 50) {
        const int f = (m - 20) / 10, s = (m - 20) % 10;
        prefetch_l2(((b >> 6) ? w3 : w1) + (size_t)(64 * s + (b & 63)) * kF + 512 * f, 1024);
    }
}

}

__global__ void __cluster_dims__(2, 1, 1) __launch_bounds__(384, 1)
fused_block_kernel(const __grid_constant__ Maps maps, const __nv_bfloat16* __restrict__ x, const __nv_bfloat16* __restrict__ wqkv,
                   const __nv_bfloat16* __restrict__ w1, const __nv_bfloat16* __restrict__ w3,
                   const __nv_bfloat16* __restrict__ wo, const __nv_bfloat16* __restrict__ w2, __nv_bfloat16* __restrict__ out) {
    extern __shared__ __align__(1024) uint8_t smem_raw[];
    const uint32_t sb = smem_u32(smem_raw);
    const int warp = __shfl_sync(0xffffffffu, threadIdx.x >> 5, 0);
    const int lane = threadIdx.x & 31;
    uint32_t rank;
    asm("mov.u32 %0, %%cluster_ctarank;" : "=r"(rank));
    const int b = blockIdx.x;
    const int pair = b >> 1;
    const int slot = pair & 7;
    const int tile = (pair >> 3) * 2 + rank;
    const int jj = slot & 3;
    const int half = slot >> 2;

    uint4 xv[5];
    unsigned cnt0 = 0;
    if (warp < 8) {
        if (threadIdx.x == 0) TRACE(0);
        const uint4* xr = reinterpret_cast<const uint4*>(x + (size_t)(tile * 128 + 16 * slot + (threadIdx.x >> 4)) * kD) + (threadIdx.x & 15);
#pragma unroll
        for (int u = 0; u < 5; u++)
            asm volatile("ld.global.nc.v4.u32 {%0,%1,%2,%3}, [%4];" : "=r"(xv[u].x), "=r"(xv[u].y), "=r"(xv[u].z), "=r"(xv[u].w) : "l"(xr + 16 * u));
        cnt0 = ld_relaxed(&g_cntO[tile * 32]);
    } else if (warp == 8) {
        TRACEG(62);
        if (elect_one()) {
#pragma unroll
            for (int i = 0; i < B_COUNT; i++) {
                uint32_t cnt = 1;
                if (i >= B_REMPTYQ && i < B_REMPTYF) cnt = 18;
                else if ((i >= B_REMPTYF && i < B_GFULL) || (i >= B_GEMPTY && i < B_CS)) cnt = 16;
                else if (i == B_HALOW) cnt = 2;
                else if (i == B_HALOR || i == B_HALOR + 1) cnt = 5;
                else if (i == B_WDONE + 1) cnt = 9;
                else if (i >= B_WDONE && i < B_FLAG) cnt = 8;
                else if (i >= B_XFREE && i < B_XN) cnt = 8;
                else if (i >= B_XN) cnt = 2;
                mbar_init(sb + SM_BAR + i * 8, cnt);
            }
            asm volatile("fence.mbarrier_init.release.cluster;" ::: "memory");
        }
        TRACE(22);
    } else {
        cnt0 = ld_relaxed(&g_cntO[tile * 32]);
        if (lane == 0) {
            if (warp == 9) { prefetch_map(&maps.x); prefetch_map(&maps.wq); prefetch_map(&maps.wqr); }
            if (warp == 10) {
#pragma unroll 1
                for (int m = 0; m < PF_DIST; m++) prefetch_stage(m, b, wqkv, w1, w3);
            }
        }
    }
    __syncthreads();
    if (warp == 8) TRACE(23);
    asm volatile("barrier.cluster.arrive.relaxed.aligned;" ::: "memory");
    if (warp == 8) {
        if (elect_one()) {
            mbar_expect_tx(sb + SM_BAR + B_XFULL * 8, 16384);
            tma3(sb + SM_X, &maps.x, 0, tile * 64, 0, sb + SM_BAR + B_XFULL * 8);
        }
        __syncwarp();
    }
    asm volatile("barrier.cluster.wait.aligned;" ::: "memory");
    if (warp == 8) TRACE(24);

    if (warp >= 8) {
        asm volatile("setmaxnreg.dec.sync.aligned.u32 56;");
        const uint32_t bar = launder(sb + SM_BAR);
        if (warp == 8) {
            const uint32_t ring = launder(sb + SM_RING);
#pragma unroll 1
            for (int n = 0; n < 20; n++) {
                const int s = n & 3;
                if (n >= 4) mbar_wait(bar + (B_REMPTYQ + s) * 8, ((n >> 2) - 1) & 1);
                const int c = (n == 1) ? 1 : (n == 3) ? 2 : (n >= 4 && n <= 16 && !(n & 1)) ? n / 2 + 1 : 0;
                if (elect_one()) {
                    mbar_expect_tx(bar + (B_RFULL + s) * 8, 15360);
                    tma3_mc(ring + s * 16384 + rank * 6144, &maps.wq, 80 * slot, 32 * n + 16 * rank, 0, bar + (B_RFULL + s) * 8);
                    tma3_mc(ring + s * 16384 + 12288 + rank * 1536, &maps.wqr, 80 * slot + 64, 32 * n + 16 * rank, 0, bar + (B_RFULL + s) * 8);
                    if (c > 0) {
                        mbar_expect_tx(bar + (B_XFULL + c) * 8, 16384);
                        tma3(sb + SM_X + c * 16384, &maps.x, c * 64, tile * 64, 0, bar + (B_XFULL + c) * 8);
                    }
                    prefetch_stage(n + PF_DIST, b, wqkv, w1, w3);
                    if (n == 8) { prefetch_map(&maps.w1); prefetch_map(&maps.w3); }
                }
                if (n == 0) TRACE(1);
            }
            const CUtensorMap* mf = rank ? &maps.w3 : &maps.w1;
            {
                int col = 64 * slot, k = 0;
#pragma unroll 1
                for (int n = 20; n < 50; n++) {
                    const int s = n & 3;
                    if (n < 24) mbar_wait(bar + (B_REMPTYQ + s) * 8, ((n >> 2) - 1) & 1);
                    else mbar_wait(bar + (B_REMPTYF + s) * 8, ((n - 24) >> 2) & 1);
                    if (elect_one()) {
                        mbar_expect_tx(bar + (B_RFULL + s) * 8, 16384);
                        tma2_mc(ring + s * 16384 + rank * 8192, mf, col, k, bar + (B_RFULL + s) * 8);
                        prefetch_stage(n + PF_DIST, b, wqkv, w1, w3);
                        if (n == 26) prefetch_l2(wo + (size_t)b * 5 * kD, 5 * kD * 2);
                        if (n == 28) prefetch_l2(w2 + (size_t)b * 12 * kD, 12 * kD * 2);
                        if (n == 32) {
                            prefetch_map(&maps.act); prefetch_map(&maps.wo2); prefetch_map(&maps.wo1); prefetch_map(&maps.w22); prefetch_map(&maps.w21);
                        }
                    }
                    k += 64;
                    if (k == 640) { k = 0; col += 512; }
                }
            }
            TRACE(2);
            int s = 0, ph = 0;
#pragma unroll 1
            for (int t = 0; t < NT_G; t++) {
                const int kc = (t < 4) ? 10 + 4 * half + t : (t < 9) ? 5 * half + t - 4 : (t < 13) ? 18 + 4 * half + t - 9 : 26 + 4 * half + t - 13;
                const int flag = (t == 0) ? 0 : (t == 4) ? 1 : (t == 9) ? 2 : (t == 13) ? 3 : -1;
                mbar_wait(bar + (B_GEMPTY + s) * 8, ph);
                if (flag >= 0) mbar_wait(bar + (B_FLAG + flag) * 8, 0);
                if (elect_one()) {
                    if (flag >= 0) fence_async_global();
                    const uint32_t st = sb + s * G_STAGE, fb = bar + (B_GFULL + s) * 8;
                    const bool isO = kc < 10;
                    const int a0 = ((isO ? kc : kc - 10) * 2 + rank) * 4;
                    mbar_expect_tx(fb, 16384 + 20480);
                    tma5_mc(st + 16384 + rank * 12288, isO ? &maps.wo2 : &maps.w22, 160 * jj, a0, fb);
                    tma4_mc(st + 16384 + rank * 12288 + 8192, isO ? &maps.wo1 : &maps.w21, 160 * jj + 128, a0, fb);
                    tma2(st, &maps.act, kc * 64, tile * 128, fb);
                }
                if (++s == 5) { s = 0; ph ^= 1; }
            }
            TRACE(3);
        } else {
            const int a = warp - 9;
            const unsigned tag = cnt0 / 8 + 1;
            const uint32_t rbar = mapa(bar, lane & 1);
            if (a == 0) {
                const int pc = 2 * tile, h = lane >> 4, kr = lane & 15;
                uint32_t o0, o1;
                if (pc < 24) {
                    o0 = h * 6144 + (pc >> 3) * 2048 + kr * 128 + (((pc & 7) ^ (kr & 7)) << 4);
                    o1 = o0 ^ 16;
                } else {
                    o0 = 12288 + h * 1536 + ((pc - 24) >> 1) * 512 + kr * 32 + (((kr >> 2) & 1) << 4);
                    o1 = o0 ^ 16;
                }
                float acc[16];
#pragma unroll
                for (int e = 0; e < 16; e++) acc[e] = 0.f;
#pragma unroll 1
                for (int n = 0; n < 20; n++) {
                    const int s = n & 3;
                    mbar_wait(bar + (B_RFULL + s) * 8, (n >> 2) & 1);
                    if (tile < 15) {
                        const uint4 v0 = lds128(sb + SM_RING + s * 16384 + o0), v1 = lds128(sb + SM_RING + s * 16384 + o1);
                        acc[0] += bf_lo(v0.x); acc[1] += bf_hi(v0.x); acc[2] += bf_lo(v0.y); acc[3] += bf_hi(v0.y);
                        acc[4] += bf_lo(v0.z); acc[5] += bf_hi(v0.z); acc[6] += bf_lo(v0.w); acc[7] += bf_hi(v0.w);
                        acc[8] += bf_lo(v1.x); acc[9] += bf_hi(v1.x); acc[10] += bf_lo(v1.y); acc[11] += bf_hi(v1.y);
                        acc[12] += bf_lo(v1.z); acc[13] += bf_hi(v1.z); acc[14] += bf_lo(v1.w); acc[15] += bf_hi(v1.w);
                    }
                    __syncwarp();
                    if (lane < 2) mbar_arrive_cluster(rbar + (B_REMPTYQ + s) * 8);
                }
                TRACE(25);
                if (tile < 15) {
                    halve<8>(acc, lane); halve<4>(acc, lane); halve<2>(acc, lane); halve<1>(acc, lane);
                    acc[0] += __shfl_xor_sync(0xffffffffu, acc[0], 1);
                    if (!(lane & 1)) st_tag(&g_cs[slot * 256 + 16 * tile + (lane >> 1)], tagged(tag, acc[0]));
                }
                {
                    unsigned long long v[8];
                    int it = 0;
#pragma unroll 1
                    while (true) {
                        bool ok = true;
#pragma unroll
                        for (int u = 0; u < 4; u++) {
                            const int n2 = lane + 32 * u;
                            if (n2 < 120) {
                                ld_tag2(&g_cs[slot * 256 + 2 * n2], v[2 * u], v[2 * u + 1]);
                                ok = ok && (uint32_t)(v[2 * u] >> 32) == tag && (uint32_t)(v[2 * u + 1] >> 32) == tag;
                            }
                        }
                        if (__all_sync(0xffffffffu, ok) || ++it > (1 << 15)) break;
                    }
#pragma unroll
                    for (int u = 0; u < 4; u++) {
                        const int n2 = lane + 32 * u;
                        if (n2 < 120) asm volatile("st.shared.v2.u32 [%0], {%1,%2};" ::"r"(sb + SM_CS + n2 * 8), "r"((uint32_t)v[2 * u]), "r"((uint32_t)v[2 * u + 1]) : "memory");
                    }
                    __syncwarp();
                    if (lane == 0) mbar_arrive(bar + B_CS * 8);
                }
                TRACE(5);
#pragma unroll 1
                for (int kb = 0; kb < 5; kb++) {
                    uint4 v[8];
#pragma unroll
                    for (int u = 0; u < 8; u++) {
                        const int idx = lane + 32 * (8 * kb + u), row = (idx * 6554) >> 16;
                        const int off = (tile * 128 + row) * kD + 80 * slot + 8 * (idx - 10 * row);
                        asm volatile("ld.global.nc.v4.u32 {%0,%1,%2,%3}, [%4];" : "=r"(v[u].x), "=r"(v[u].y), "=r"(v[u].z), "=r"(v[u].w) : "l"(x + off));
                    }
#pragma unroll
                    for (int u = 0; u < 8; u++) {
                        const int idx = lane + 32 * (8 * kb + u), row = (idx * 6554) >> 16;
                        const int off = (tile * 128 + row) * kD + 80 * slot + 8 * (idx - 10 * row);
                        *reinterpret_cast<uint4*>(out + off) = v[u];
                    }
                }
                __syncwarp();
                if (lane == 0) mbar_arrive(bar + (B_WDONE + 1) * 8);
                TRACE(7);
            } else {
                if (a == 1) {
                    unsigned long long v[8];
                    int it = 0;
#pragma unroll 1
                    while (true) {
                        bool ok = true;
#pragma unroll
                        for (int u = 0; u < 4; u++) {
                            const int rho = lane + 32 * u;
                            ld_tag2(&g_stats[(size_t)(tile * 128 + 2 * (rho & 63) + (rho >> 6)) * 2], v[2 * u], v[2 * u + 1]);
                            ok = ok && (uint32_t)(v[2 * u] >> 32) == tag && (uint32_t)(v[2 * u + 1] >> 32) == tag;
                        }
                        if (__all_sync(0xffffffffu, ok) || ++it > (1 << 15)) break;
                    }
#pragma unroll
                    for (int u = 0; u < 4; u++) {
                        const int rho = lane + 32 * u;
                        const float r = __uint_as_float((uint32_t)v[2 * u]), m = __uint_as_float((uint32_t)v[2 * u + 1]);
                        asm volatile("st.shared.v2.f32 [%0], {%1,%2};" ::"r"(sb + SM_ST + rho * 8), "f"(r), "f"(-m * r) : "memory");
                        asm volatile("st.shared.u32 [%0], %1;" ::"r"(sb + SM_NM + rho * 4), "r"(pack2(-m, -m)) : "memory");
                    }
                    __syncwarp();
                    if (lane == 0) mbar_arrive(bar + B_ST * 8);
                    TRACE(6);
                }
                mbar_wait(bar + B_ST * 8, 0);
                {
                    const int t64 = (a - 1) * 32 + lane;
                    uint32_t nm[16];
#pragma unroll
                    for (int k = 0; k < 16; k++) nm[k] = lds32(sb + SM_NM + ((t64 >> 3) + 8 * k) * 4);
#pragma unroll 1
                    for (int c = 0; c < 10; c++) {
                        const uint32_t base = sb + SM_X + c * 16384 + t64 * 16;
                        mbar_wait(bar + (B_XFREE + c) * 8, 0);
                        if (a == 1) TRACE(140 + c);
#pragma unroll
                        for (int kb = 0; kb < 4; kb++) {
                            uint4 v[4];
#pragma unroll
                            for (int u = 0; u < 4; u++) v[u] = lds128(base + (4 * kb + u) * 1024);
#pragma unroll
                            for (int u = 0; u < 4; u++) {
                                const uint32_t m = nm[4 * kb + u];
                                sts128(base + (4 * kb + u) * 1024, make_uint4(badd2(v[u].x, m), badd2(v[u].y, m), badd2(v[u].z, m), badd2(v[u].w, m)));
                            }
                        }
                        if (a == 1) TRACE(150 + c);
                        asm volatile("fence.proxy.async.shared::cta;" ::: "memory");
                        __syncwarp();
                        if (lane == 0) mbar_arrive(bar + (B_XN + c) * 8);
                    }
                }
                if (a == 1) {
                    TRACE(4);
                    mbar_wait(bar + B_HALOW * 8, 0);
                    if (lane == 0) {
                        if (tile < 15) { fence_gpu(); st_relaxed(&g_flagHalo[(tile * 8 + slot) * 32], tag); }
                        if (tile > 0) poll_ge(&g_flagHalo[((tile - 1) * 8 + slot) * 32], tag);
                        mbar_arrive(bar + B_HALOR * 8);
                        mbar_arrive(bar + (B_HALOR + 1) * 8);
                        const unsigned tgt = tag * 8;
                        poll_ge(&g_cntH[(tile * 3 + 0) * 32], tgt);
                        mbar_arrive(bar + (B_FLAG + 0) * 8);
                        poll_ge(&g_cntO[tile * 32], tgt);
                        mbar_arrive(bar + (B_FLAG + 1) * 8);
                        poll_ge(&g_cntH[(tile * 3 + 1) * 32], tgt);
                        mbar_arrive(bar + (B_FLAG + 2) * 8);
                        poll_ge(&g_cntH[(tile * 3 + 2) * 32], tgt);
                        mbar_arrive(bar + (B_FLAG + 3) * 8);
                    }
                } else {
#pragma unroll 1
                    for (int r = 0; r < 4; r++) {
                        mbar_wait(bar + (B_WDONE + r) * 8, 0);
                        unsigned* cnt = (r == 1) ? &g_cntO[tile * 32] : &g_cntH[(tile * 3 + (r == 0 ? 0 : r - 1)) * 32];
                        if (lane == 0) { fence_async_global(); fence_gpu(); red_add(cnt, 1); }
                    }
                }
            }
        }
    } else {
        asm volatile("setmaxnreg.inc.sync.aligned.u32 224;");
        {
            float f[40];
#pragma unroll
            for (int u = 0; u < 5; u++) {
                f[8 * u + 0] = bf_lo(xv[u].x); f[8 * u + 1] = bf_hi(xv[u].x); f[8 * u + 2] = bf_lo(xv[u].y); f[8 * u + 3] = bf_hi(xv[u].y);
                f[8 * u + 4] = bf_lo(xv[u].z); f[8 * u + 5] = bf_hi(xv[u].z); f[8 * u + 6] = bf_lo(xv[u].w); f[8 * u + 7] = bf_hi(xv[u].w);
            }
            float s4[4] = {0.f, 0.f, 0.f, 0.f};
#pragma unroll
            for (int e = 0; e < 40; e++) s4[e & 3] += f[e];
            float s = (s4[0] + s4[1]) + (s4[2] + s4[3]);
#pragma unroll
            for (int o = 1; o < 16; o <<= 1) s += __shfl_xor_sync(0xffffffffu, s, o);
            const float mean = s * (1.f / kD);
            float q4[4] = {0.f, 0.f, 0.f, 0.f};
#pragma unroll
            for (int e = 0; e < 40; e++) { const float d = f[e] - mean; q4[e & 3] = fmaf(d, d, q4[e & 3]); }
            float ss = (q4[0] + q4[1]) + (q4[2] + q4[3]);
#pragma unroll
            for (int o = 1; o < 16; o <<= 1) ss += __shfl_xor_sync(0xffffffffu, ss, o);
            if ((lane & 15) == 0) {
                const unsigned tag = cnt0 / 8 + 1;
                const float r = 1.f / sqrtf(ss * (1.f / kD) + 1e-5f);
                st_tag2(&g_stats[(size_t)(tile * 128 + 16 * slot + (threadIdx.x >> 4)) * 2], tagged(tag, r), tagged(tag, mean));
            }
            if (warp == 0) TRACE(26);
        }
        Ctx c;
        c.sb = sb;
        c.bar = sb + SM_BAR;
        c.lane = lane; c.q = lane & 3; c.g = lane >> 2; c.w = warp & 3; c.par = warp >> 2;
        c.rbar = mapa(c.bar, lane & 1);
        c.a_lo = ((sb & 0x3FFFF) >> 4) + c.par * 512 + lbo(16);
        c.b_lo = ((sb + SM_RING) & 0x3FFFF) >> 4;
        const int idx0 = c.w * 16 + c.g;
        const int tok0 = tile * 128 + 2 * idx0 + c.par;
        __nv_bfloat16* actrow = g_act + (size_t)(tile * 128 + c.par * 64 + idx0) * kActLd + 8 * c.q;

        float q1[96], q2[24];
#pragma unroll
        for (int n = 0; n < 20; n++) {
            if ((n & 1) == 0) mbar_wait(c.bar + (B_XFULL + n / 2) * 8, 0);
            mbar_wait(c.bar + (B_RFULL + (n & 3)) * 8, (n >> 2) & 1);
            if (n == 0 && c.w == 0) TRACE(8 + c.par);
            if (warp == 0) TRACE(64 + n);
            wg_fence();
#pragma unroll
            for (int h = 0; h < 2; h++) {
                const uint32_t alo = c.a_lo + (n >> 1) * 1024 + ((n & 1) * 2 + h) * 2;
                wgmma_n192(q1, alo, HI_128, c.b_lo + lbo(2048) + (n & 3) * 1024 + h * 384, HI_128, (n | h) != 0);
                wgmma_n48(q2, alo, HI_128, c.b_lo + lbo(512) + (n & 3) * 1024 + 768 + h * 96, HI_32, (n | h) != 0);
            }
            wg_commit();
            wg_wait<1>();
            if (n > 0) arrive_both(c, B_REMPTYQ + ((n - 1) & 3));
            if (n >= 2 && (n & 1) == 0 && lane == 0) mbar_arrive(c.bar + (B_XFREE + n / 2 - 1) * 8);
        }
        if (c.w == 0) TRACE(10 + c.par);

        float accA[64], accB[64];
        uint32_t qp[20], kp[20], vp[20], hk[10], hv[10], op[20], hp[8];
        const bool first = (tile == 0) && (c.w == 0);
        f_issue<20>(c, accA);
        {
            mbar_wait(c.bar + B_ST * 8, 0);
            const float2 s0 = lds64(sb + SM_ST + (c.par * 64 + idx0) * 8), s1 = lds64(sb + SM_ST + (c.par * 64 + idx0 + 8) * 8);
            c.r0 = s0.x; c.n0 = s0.y; c.r1 = s1.x; c.n1 = s1.y;
        }
        f_issue<21>(c, accA); mbar_wait(c.bar + B_CS * 8, 0); qkv_pack<1, 0, 3>(c, q1, q2, kp);
        f_issue<22>(c, accA); qkv_pack<1, 3, 7>(c, q1, q2, kp);
        f_issue<23>(c, accA); qkv_pack<1, 7, 10>(c, q1, q2, kp);
        f_issue<24>(c, accA); qkv_pack<2, 0, 3>(c, q1, q2, vp);
        f_issue<25>(c, accA); qkv_pack<2, 3, 7>(c, q1, q2, vp);
        f_issue<26>(c, accA); qkv_pack<2, 7, 10>(c, q1, q2, vp);
        {
            const int dt = (c.w == 3) ? tile + 1 : tile, dw = (c.w + 1) & 3;
            if (dt < 16) {
                uint4* hq = g_halo + (size_t)(((dt * 8 + slot) * 2 + c.par) * 4 + dw) * 160 + lane;
                hq[0] = make_uint4(kp[1], kp[3], kp[5], kp[7]);
                hq[32] = make_uint4(kp[9], kp[11], kp[13], kp[15]);
                hq[64] = make_uint4(kp[17], kp[19], vp[1], vp[3]);
                hq[96] = make_uint4(vp[5], vp[7], vp[9], vp[11]);
                hq[128] = make_uint4(vp[13], vp[15], vp[17], vp[19]);
            }
            __syncwarp();
            if (lane == 0) {
                mbar_arrive(c.bar + (B_HALOR + c.par) * 8);
                if (c.w == 3) mbar_arrive(c.bar + B_HALOW * 8);
            }
        }
        f_issue<27>(c, accA); qkv_pack<0, 0, 3>(c, q1, q2, qp);
        f_issue<28>(c, accA); qkv_pack<0, 3, 7>(c, q1, q2, qp);
        f_issue<29>(c, accA); qkv_pack<0, 7, 10>(c, q1, q2, qp);
        c.ga0 = 0.5f * c.r0; c.ga1 = 0.5f * c.r1; c.gb0 = c.ga0 * c.r0; c.gb1 = c.ga1 * c.r1;
        if (c.w == 0) TRACE(12 + c.par);

        __nv_bfloat16* hrow0 = actrow + kD + 64 * slot;
        f_issue<30>(c, accB); swiglu_groups<0, 2>(c, accA, hp, hrow0);
        f_issue<31>(c, accB); swiglu_groups<2, 4>(c, accA, hp, hrow0);
        f_issue<32>(c, accB); swiglu_groups<4, 6>(c, accA, hp, hrow0);
        f_issue<33>(c, accB); swiglu_groups<6, 8>(c, accA, hp, hrow0);
        arrive_local(c, B_WDONE + 0);
        f_issue<34>(c, accB);
        {
            mbar_wait(c.bar + (B_HALOR + c.par) * 8, 0);
            const uint4* hq = g_halo + (size_t)(((tile * 8 + slot) * 2 + c.par) * 4 + c.w) * 160 + lane;
            uint4 t0 = make_uint4(0, 0, 0, 0), t1 = t0, t2 = t0, t3 = t0, t4 = t0;
            if (!first) { t0 = __ldcg(hq); t1 = __ldcg(hq + 32); t2 = __ldcg(hq + 64); t3 = __ldcg(hq + 96); t4 = __ldcg(hq + 128); }
            hk[0] = t0.x; hk[1] = t0.y; hk[2] = t0.z; hk[3] = t0.w; hk[4] = t1.x; hk[5] = t1.y; hk[6] = t1.z; hk[7] = t1.w;
            hk[8] = t2.x; hk[9] = t2.y; hv[0] = t2.z; hv[1] = t2.w; hv[2] = t3.x; hv[3] = t3.y; hv[4] = t3.z; hv[5] = t3.w;
            hv[6] = t4.x; hv[7] = t4.y; hv[8] = t4.z; hv[9] = t4.w;
        }
        float sc[4][4], mx[4][2];
        uint32_t pr[4][4];
        f_issue<35>(c, accB);
        attn_logits<0>(c, first, qp, kp, hk, sc[0]); attn_logits<1>(c, first, qp, kp, hk, sc[1]);
        attn_logits<2>(c, first, qp, kp, hk, sc[2]); attn_logits<3>(c, first, qp, kp, hk, sc[3]);
        f_issue<36>(c, accB); attn_max(sc, mx);
        f_issue<37>(c, accB); attn_exp(sc, mx);
        f_issue<38>(c, accB); attn_sum(mx);
        f_issue<39>(c, accB); attn_probs(c, sc, mx, pr);
        if (c.w == 0) TRACE(14 + c.par);

        f_issue<40>(c, accA); attn_pv<0>(c, pr[0], vp, hv, op); attn_pv<1>(c, pr[1], vp, hv, op);
        f_issue<41>(c, accA); attn_pv<2>(c, pr[2], vp, hv, op); attn_pv<3>(c, pr[3], vp, hv, op);
        f_issue<42>(c, accA);
        {
            __nv_bfloat16* orow = actrow + 160 * (slot >> 1);
            if ((slot & 1) == 0) {
                stg128(orow, op[0], op[2], op[4], op[6]);
                stg128(orow + 8 * kActLd, op[1], op[3], op[5], op[7]);
                stg128(orow + 32, op[8], op[10], op[12], op[14]);
                stg128(orow + 8 * kActLd + 32, op[9], op[11], op[13], op[15]);
                *reinterpret_cast<uint2*>(orow + 64) = make_uint2(op[16], op[18]);
                *reinterpret_cast<uint2*>(orow + 8 * kActLd + 64) = make_uint2(op[17], op[19]);
            } else {
                *reinterpret_cast<uint2*>(orow + 68) = make_uint2(op[0], op[2]);
                *reinterpret_cast<uint2*>(orow + 8 * kActLd + 68) = make_uint2(op[1], op[3]);
                stg128(orow + 96, op[4], op[6], op[8], op[10]);
                stg128(orow + 8 * kActLd + 96, op[5], op[7], op[9], op[11]);
                stg128(orow + 128, op[12], op[14], op[16], op[18]);
                stg128(orow + 8 * kActLd + 128, op[13], op[15], op[17], op[19]);
            }
            arrive_local(c, B_WDONE + 1);
        }
        swiglu_groups<0, 1>(c, accB, hp, hrow0 + 512);
        f_issue<43>(c, accA); swiglu_groups<1, 2>(c, accB, hp, hrow0 + 512);
        f_issue<44>(c, accA); swiglu_groups<2, 3>(c, accB, hp, hrow0 + 512);
        f_issue<45>(c, accA); swiglu_groups<3, 4>(c, accB, hp, hrow0 + 512);
        f_issue<46>(c, accA); swiglu_groups<4, 5>(c, accB, hp, hrow0 + 512);
        f_issue<47>(c, accA); swiglu_groups<5, 6>(c, accB, hp, hrow0 + 512);
        f_issue<48>(c, accA); swiglu_groups<6, 7>(c, accB, hp, hrow0 + 512);
        f_issue<49>(c, accA); swiglu_groups<7, 8>(c, accB, hp, hrow0 + 512);
        arrive_local(c, B_WDONE + 2);
        if (c.w == 0) TRACE(16 + c.par);

        float accG[80];
        g_issue(c, accG, 0, 0, true, 0);
        wg_wait<1>();
        arrive_both(c, B_GEMPTY + 3);
        arrive_both(c, B_GEMPTY + 4);
        swiglu_groups<0, 2>(c, accA, hp, hrow0 + 1024);
        g_issue(c, accG, 1, 0, false, 1); wg_wait<1>(); arrive_both(c, B_GEMPTY + 0);
        swiglu_groups<2, 4>(c, accA, hp, hrow0 + 1024);
        g_issue(c, accG, 2, 0, false, 2); wg_wait<1>(); arrive_both(c, B_GEMPTY + 1);
        swiglu_groups<4, 6>(c, accA, hp, hrow0 + 1024);
        g_issue(c, accG, 3, 0, false, 3); wg_wait<1>(); arrive_both(c, B_GEMPTY + 2);
        swiglu_groups<6, 8>(c, accA, hp, hrow0 + 1024);
        arrive_local(c, B_WDONE + 3);
        g_issue(c, accG, 4, 0, false, 4); wg_wait<1>(); arrive_both(c, B_GEMPTY + 3);
        int gs = 0, gph = 1;
#pragma unroll 1
        for (int t = 5; t < NT_G; t++) {
            g_issue(c, accG, gs, gph, false, t);
            wg_wait<1>();
            if (t + 4 < NT_G) arrive_both(c, B_GEMPTY + (gs == 0 ? 4 : gs - 1));
            if (++gs == 5) { gs = 0; gph ^= 1; }
        }
        if (c.w == 0) TRACE(18 + c.par);
        __nv_bfloat16* orow = out + (size_t)tok0 * kD + 160 * jj;
        wg_wait<0>();
#pragma unroll
        for (int p = 0; p < 10; p++) {
            const int G = 2 * p;
            red_pair(orow + 16 * p, c.q, pack2(accG[4 * G], accG[4 * G + 1]), pack2(accG[4 * G + 4], accG[4 * G + 5]));
            red_pair(orow + 16 * kD + 16 * p, c.q, pack2(accG[4 * G + 2], accG[4 * G + 3]), pack2(accG[4 * G + 6], accG[4 * G + 7]));
        }
        if (c.w == 0) { TRACE(20 + c.par); TRACEG(60 + c.par); }
    }
}

namespace {
typedef CUresult (*EncodeFn)(CUtensorMap*, CUtensorMapDataType, cuuint32_t, void*, const cuuint64_t*, const cuuint64_t*, const cuuint32_t*,
                             const cuuint32_t*, CUtensorMapInterleave, CUtensorMapSwizzle, CUtensorMapL2promotion, CUtensorMapFloatOOBfill);

bool encode(EncodeFn fn, CUtensorMap* m, const void* ptr, int rank, const cuuint64_t* dims, const cuuint64_t* strides, const cuuint32_t* box,
            CUtensorMapSwizzle sw) {
    const cuuint32_t es[5] = {1, 1, 1, 1, 1};
    return fn(m, CU_TENSOR_MAP_DATA_TYPE_BFLOAT16, rank, const_cast<void*>(ptr), dims, strides, box, es, CU_TENSOR_MAP_INTERLEAVE_NONE, sw,
              CU_TENSOR_MAP_L2_PROMOTION_L2_128B, CU_TENSOR_MAP_FLOAT_OOB_FILL_NONE) == CUDA_SUCCESS;
}
}

extern "C" void kernel_launch(void* const* d_in, const int* in_sizes, int n_in, void* d_out, int out_size) {
    (void)in_sizes; (void)n_in; (void)out_size;
    const __nv_bfloat16* x = (const __nv_bfloat16*)d_in[0];
    const __nv_bfloat16* wqkv = (const __nv_bfloat16*)d_in[1];
    const __nv_bfloat16* wo = (const __nv_bfloat16*)d_in[2];
    const __nv_bfloat16* w1 = (const __nv_bfloat16*)d_in[4];
    const __nv_bfloat16* w3 = (const __nv_bfloat16*)d_in[5];
    const __nv_bfloat16* w2 = (const __nv_bfloat16*)d_in[6];

    static EncodeFn fn = nullptr;
    static void* act = nullptr;
    if (!fn) {
        void* p = nullptr;
        cudaDriverEntryPointQueryResult st;
        cudaGetDriverEntryPoint("cuTensorMapEncodeTiled", &p, cudaEnableDefault, &st);
        fn = (EncodeFn)p;
        cudaFuncSetAttribute(fused_block_kernel, cudaFuncAttributeMaxDynamicSharedMemorySize, SM_TOTAL);
        cudaGetSymbolAddress(&act, g_act);
    }
    Maps maps;
    {
        const cuuint64_t d[3] = {640, 1024, 2}, s[2] = {2560, 1280};
        const cuuint32_t b[3] = {64, 64, 2};
        encode(fn, &maps.x, x, 3, d, s, b, CU_TENSOR_MAP_SWIZZLE_128B);
    }
    {
        const cuuint64_t d[3] = {640, 640, 3}, s[2] = {3840, 1280};
        const cuuint32_t b[3] = {64, 16, 3}, br[3] = {16, 16, 3};
        encode(fn, &maps.wq, wqkv, 3, d, s, b, CU_TENSOR_MAP_SWIZZLE_128B);
        encode(fn, &maps.wqr, wqkv, 3, d, s, br, CU_TENSOR_MAP_SWIZZLE_32B);
    }
    {
        const cuuint64_t d[2] = {1536, 640}, s[1] = {3072};
        const cuuint32_t b[2] = {64, 64};
        encode(fn, &maps.w1, w1, 2, d, s, b, CU_TENSOR_MAP_SWIZZLE_128B);
        encode(fn, &maps.w3, w3, 2, d, s, b, CU_TENSOR_MAP_SWIZZLE_128B);
    }
    {
        const cuuint64_t d[2] = {(cuuint64_t)kActLd, (cuuint64_t)kS}, s[1] = {(cuuint64_t)kActLd * 2};
        const cuuint32_t b[2] = {64, 128};
        encode(fn, &maps.act, act, 2, d, s, b, CU_TENSOR_MAP_SWIZZLE_128B);
    }
    {
        const cuuint64_t do5[5] = {640, 2, 80, 4, 2}, d25[5] = {640, 2, 192, 4, 2}, s5[4] = {1280, 10240, 2560, 128};
        const cuuint32_t b5[5] = {64, 2, 4, 4, 2}, b4[4] = {32, 2, 4, 4};
        encode(fn, &maps.wo2, wo, 5, do5, s5, b5, CU_TENSOR_MAP_SWIZZLE_128B);
        encode(fn, &maps.w22, w2, 5, d25, s5, b5, CU_TENSOR_MAP_SWIZZLE_128B);
        encode(fn, &maps.wo1, wo, 4, do5, s5, b4, CU_TENSOR_MAP_SWIZZLE_128B);
        encode(fn, &maps.w21, w2, 4, d25, s5, b4, CU_TENSOR_MAP_SWIZZLE_128B);
    }
    fused_block_kernel<<<128, 384, SM_TOTAL>>>(maps, x, wqkv, w1, w3, wo, w2, (__nv_bfloat16*)d_out);
}
```

```cpp
#include <cuda_runtime.h>
#include <cuda_bf16.h>
#include <cuda.h>
#include <stdint.h>

namespace {

constexpr int kS = 2048, kD = 640, kF = 1536;
constexpr int kActLd = kD + kF;

constexpr uint32_t SM_X = 0;
constexpr uint32_t SM_RING = 163840;
constexpr uint32_t SM_MISC = 229376;
constexpr uint32_t SM_BAR = SM_MISC;
constexpr uint32_t SM_CS = SM_MISC + 576;
constexpr uint32_t SM_ST = SM_CS + 960;
constexpr uint32_t SM_NM = SM_ST + 1024;
constexpr uint32_t SM_TOTAL = 232448;
constexpr uint32_t G_STAGE = 40960;
static_assert(SM_NM + 512 <= SM_TOTAL, "smem map");

constexpr int B_XFULL = 0;
constexpr int B_RFULL = 10;
constexpr int B_REMPTYQ = 14;
constexpr int B_REMPTYF = 18;
constexpr int B_GFULL = 22;
constexpr int B_GEMPTY = 27;
constexpr int B_CS = 32;
constexpr int B_ST = 33;
constexpr int B_HALOW = 34;
constexpr int B_HALOR = 35;
constexpr int B_WDONE = 37;
constexpr int B_FLAG = 41;
constexpr int B_XFREE = 45;
constexpr int B_XN = 55;
constexpr int B_COUNT = 65;

#define NO0 4
constexpr int PF_DIST = 6;
#define SILU_TANH 1

__device__ __align__(1024) __nv_bfloat16 g_act[kS * kActLd];
__device__ __align__(128) unsigned long long g_cs[8 * 256];
__device__ __align__(128) unsigned long long g_stats[kS * 2];
__device__ __align__(128) uint4 g_halo[16 * 8 * 2 * 4 * 5 * 32];
__device__ __align__(128) unsigned g_cntO[16 * 32];
__device__ __align__(128) unsigned g_cntH[16 * 3 * 32];
__device__ __align__(128) unsigned g_flagHalo[16 * 8 * 32];
#define TRACE(slot) do { } while (0)
#define TRACEG(slot) do { } while (0)

struct Maps {
    CUtensorMap x, wq, wqr, w1, w3, act, wo2, wo1, w22, w21, o64, o32;
};

__device__ __forceinline__ long long gtime() { long long t; asm volatile("mov.u64 %0, %%globaltimer;" : "=l"(t)); return t; }
__device__ __forceinline__ uint32_t smem_u32(const void* p) { return (uint32_t)__cvta_generic_to_shared(p); }
__device__ __forceinline__ uint32_t launder(uint32_t x) { uint32_t y; asm volatile("mov.u32 %0, %1;" : "=r"(y) : "r"(x)); return y; }
__device__ __forceinline__ bool elect_one() {
    uint32_t p;
    asm volatile("{\n.reg .pred P;\nelect.sync _|P, 0xffffffff;\nselp.u32 %0,1,0,P;\n}" : "=r"(p));
    return p;
}
__device__ __forceinline__ void mbar_init(uint32_t bar, uint32_t cnt) { asm volatile("mbarrier.init.shared::cta.b64 [%0], %1;" ::"r"(bar), "r"(cnt)); }
__device__ __forceinline__ void mbar_expect_tx(uint32_t bar, uint32_t bytes) {
    asm volatile("mbarrier.arrive.expect_tx.shared::cta.b64 _, [%0], %1;" ::"r"(bar), "r"(bytes) : "memory");
}
__device__ __forceinline__ void mbar_arrive(uint32_t bar) { asm volatile("mbarrier.arrive.shared::cta.b64 _, [%0];" ::"r"(bar) : "memory"); }
__device__ __forceinline__ void mbar_arrive_cluster(uint32_t bar_cluster_addr) {
    asm volatile("mbarrier.arrive.shared::cluster.b64 _, [%0];" ::"r"(bar_cluster_addr) : "memory");
}
__device__ __forceinline__ uint32_t mapa(uint32_t addr, uint32_t cta) {
    uint32_t r; asm("mapa.shared::cluster.u32 %0, %1, %2;" : "=r"(r) : "r"(addr), "r"(cta)); return r;
}
__device__ __forceinline__ bool mbar_try(uint32_t bar, uint32_t parity) {
    uint32_t ok;
    asm volatile("{\n.reg .pred p;\nmbarrier.try_wait.parity.shared::cta.b64 p, [%1], %2;\nselp.u32 %0,1,0,p;\n}"
                 : "=r"(ok) : "r"(bar), "r"(parity) : "memory");
    return ok;
}
__device__ __forceinline__ void mbar_wait(uint32_t bar, uint32_t parity) {
    int it = 0;
#pragma unroll 1
    while (!mbar_try(bar, parity)) { if (++it > (1 << 17)) break; }
}
__device__ __forceinline__ void tma2(uint32_t dst, const CUtensorMap* m, int c0, int c1, uint32_t bar) {
    asm volatile("cp.async.bulk.tensor.2d.shared::cluster.global.mbarrier::complete_tx::bytes [%0], [%1, {%3, %4}], [%2];"
                 ::"r"(dst), "l"(m), "r"(bar), "r"(c0), "r"(c1) : "memory");
}
__device__ __forceinline__ void tma3(uint32_t dst, const CUtensorMap* m, int c0, int c1, int c2, uint32_t bar) {
    asm volatile("cp.async.bulk.tensor.3d.shared::cluster.global.mbarrier::complete_tx::bytes [%0], [%1, {%3, %4, %5}], [%2];"
                 ::"r"(dst), "l"(m), "r"(bar), "r"(c0), "r"(c1), "r"(c2) : "memory");
}
__device__ __forceinline__ void tma2_mc(uint32_t dst, const CUtensorMap* m, int c0, int c1, uint32_t bar) {
    asm volatile("cp.async.bulk.tensor.2d.shared::cluster.global.mbarrier::complete_tx::bytes.multicast::cluster [%0], [%1, {%3, %4}], [%2], %5;"
                 ::"r"(dst), "l"(m), "r"(bar), "r"(c0), "r"(c1), "h"((uint16_t)3) : "memory");
}
__device__ __forceinline__ void tma3_mc(uint32_t dst, const CUtensorMap* m, int c0, int c1, int c2, uint32_t bar) {
    asm volatile("cp.async.bulk.tensor.3d.shared::cluster.global.mbarrier::complete_tx::bytes.multicast::cluster [%0], [%1, {%3, %4, %5}], [%2], %6;"
                 ::"r"(dst), "l"(m), "r"(bar), "r"(c0), "r"(c1), "r"(c2), "h"((uint16_t)3) : "memory");
}
__device__ __forceinline__ void tma4_mc(uint32_t dst, const CUtensorMap* m, int c0, int c2, uint32_t bar) {
    asm volatile("cp.async.bulk.tensor.4d.shared::cluster.global.mbarrier::complete_tx::bytes.multicast::cluster [%0], [%1, {%3, %5, %4, %5}], [%2], %6;"
                 ::"r"(dst), "l"(m), "r"(bar), "r"(c0), "r"(c2), "r"(0), "h"((uint16_t)3) : "memory");
}
__device__ __forceinline__ void tma5_mc(uint32_t dst, const CUtensorMap* m, int c0, int c2, uint32_t bar) {
    asm volatile("cp.async.bulk.tensor.5d.shared::cluster.global.mbarrier::complete_tx::bytes.multicast::cluster [%0], [%1, {%3, %5, %4, %5, %5}], [%2], %6;"
                 ::"r"(dst), "l"(m), "r"(bar), "r"(c0), "r"(c2), "r"(0), "h"((uint16_t)3) : "memory");
}
__device__ __forceinline__ void bulk_g2s(uint32_t dst, const void* src, uint32_t bytes, uint32_t bar) {
    asm volatile("cp.async.bulk.shared::cluster.global.mbarrier::complete_tx::bytes [%0], [%1], %2, [%3];"
                 ::"r"(dst), "l"(src), "r"(bytes), "r"(bar) : "memory");
}
__device__ __forceinline__ uint4 lds128(uint32_t a) {
    uint4 v; asm volatile("ld.shared.v4.u32 {%0,%1,%2,%3}, [%4];" : "=r"(v.x), "=r"(v.y), "=r"(v.z), "=r"(v.w) : "r"(a) : "memory"); return v;
}
__device__ __forceinline__ void sts128(uint32_t a, uint4 v) {
    asm volatile("st.shared.v4.u32 [%0], {%1,%2,%3,%4};" ::"r"(a), "r"(v.x), "r"(v.y), "r"(v.z), "r"(v.w) : "memory");
}
__device__ __forceinline__ void prefetch_map(const CUtensorMap* m) { asm volatile("prefetch.tensormap [%0];" ::"l"(m) : "memory"); }
__device__ __forceinline__ void prefetch_l2(const void* p, uint32_t bytes) {
    asm volatile("cp.async.bulk.prefetch.L2.global [%0], %1;" ::"l"(p), "r"(bytes) : "memory");
}
__device__ __forceinline__ void wg_fence() { asm volatile("wgmma.fence.sync.aligned;" ::: "memory"); }
__device__ __forceinline__ void wg_commit() { asm volatile("wgmma.commit_group.sync.aligned;" ::: "memory"); }
template <int N> __device__ __forceinline__ void wg_wait() { asm volatile("wgmma.wait_group.sync.aligned %0;" ::"n"(N) : "memory"); }
__device__ __forceinline__ unsigned ld_acquire(const unsigned* p) {
    unsigned v; asm volatile("ld.acquire.gpu.global.u32 %0, [%1];" : "=r"(v) : "l"(p) : "memory"); return v;
}
__device__ __forceinline__ void fence_gpu() { asm volatile("fence.acq_rel.gpu;" ::: "memory"); }
__device__ __forceinline__ void fence_async_global() { asm volatile("fence.proxy.async.global;" ::: "memory"); }
__device__ __forceinline__ void red_add(unsigned* p, unsigned v) { asm volatile("red.relaxed.gpu.global.add.u32 [%0], %1;" ::"l"(p), "r"(v) : "memory"); }
__device__ __forceinline__ void st_relaxed(unsigned* p, unsigned v) { asm volatile("st.relaxed.gpu.global.u32 [%0], %1;" ::"l"(p), "r"(v) : "memory"); }
__device__ __forceinline__ unsigned ld_relaxed(const unsigned* p) {
    unsigned v; asm volatile("ld.relaxed.gpu.global.u32 %0, [%1];" : "=r"(v) : "l"(p) : "memory"); return v;
}
__device__ __forceinline__ unsigned long long tagged(unsigned tag, float v) { return ((unsigned long long)tag << 32) | __float_as_uint(v); }
__device__ __forceinline__ void st_tag2(unsigned long long* p, unsigned long long a, unsigned long long b) {
    asm volatile("st.relaxed.gpu.global.v2.b64 [%0], {%1, %2};" ::"l"(p), "l"(a), "l"(b) : "memory");
}
__device__ __forceinline__ void st_tag(unsigned long long* p, unsigned long long a) {
    asm volatile("st.relaxed.gpu.global.b64 [%0], %1;" ::"l"(p), "l"(a) : "memory");
}
__device__ __forceinline__ void ld_tag2(const unsigned long long* p, unsigned long long& a, unsigned long long& b) {
    asm volatile("ld.relaxed.gpu.global.v2.b64 {%0, %1}, [%2];" : "=l"(a), "=l"(b) : "l"(p) : "memory");
}
__device__ __forceinline__ void poll_ge(const unsigned* p, unsigned target) {
    int it = 0;
#pragma unroll 1
    while ((int)(ld_acquire(p) - target) < 0) { if (++it > (1 << 16)) break; }
}
template <int ID, int N> __device__ __forceinline__ void bar_sync() { asm volatile("bar.sync %0, %1;" ::"n"(ID), "n"(N) : "memory"); }
__device__ __forceinline__ float ex2(float x) { float y; asm("ex2.approx.ftz.f32 %0, %1;" : "=f"(y) : "f"(x)); return y; }
__device__ __forceinline__ float rcp(float x) { float y; asm("rcp.approx.ftz.f32 %0, %1;" : "=f"(y) : "f"(x)); return y; }
__device__ __forceinline__ float tanh_fast(float x) { float y; asm("tanh.approx.f32 %0, %1;" : "=f"(y) : "f"(x)); return y; }
__device__ __forceinline__ uint32_t badd2(uint32_t a, uint32_t b) { uint32_t d; asm("add.rn.bf16x2 %0, %1, %2;" : "=r"(d) : "r"(a), "r"(b)); return d; }
__device__ __forceinline__ uint32_t lds32(uint32_t a) { uint32_t v; asm volatile("ld.shared.u32 %0, [%1];" : "=r"(v) : "r"(a) : "memory"); return v; }
__device__ __forceinline__ uint32_t pack2(float lo, float hi) {
    uint32_t r; asm("cvt.rn.bf16x2.f32 %0, %1, %2;" : "=r"(r) : "f"(hi), "f"(lo)); return r;
}
__device__ __forceinline__ float bf_lo(uint32_t v) { return __uint_as_float(v << 16); }
__device__ __forceinline__ float bf_hi(uint32_t v) { return __uint_as_float(v & 0xffff0000u); }
__device__ __forceinline__ float2 lds64(uint32_t a) { float2 v; asm volatile("ld.shared.v2.f32 {%0,%1}, [%2];" : "=f"(v.x), "=f"(v.y) : "r"(a)); return v; }
__device__ __forceinline__ void mma16(float (&c)[4], uint32_t a0, uint32_t a1, uint32_t a2, uint32_t a3, uint32_t b0, uint32_t b1) {
    asm("mma.sync.aligned.m16n8k16.row.col.f32.bf16.bf16.f32 {%0,%1,%2,%3}, {%4,%5,%6,%7}, {%8,%9}, {%0,%1,%2,%3};"
        : "+f"(c[0]), "+f"(c[1]), "+f"(c[2]), "+f"(c[3]) : "r"(a0), "r"(a1), "r"(a2), "r"(a3), "r"(b0), "r"(b1));
}
__device__ __forceinline__ void mma8(float (&c)[4], uint32_t a0, uint32_t a1, uint32_t b0) {
    asm("mma.sync.aligned.m16n8k8.row.col.f32.bf16.bf16.f32 {%0,%1,%2,%3}, {%4,%5}, {%6}, {%0,%1,%2,%3};"
        : "+f"(c[0]), "+f"(c[1]), "+f"(c[2]), "+f"(c[3]) : "r"(a0), "r"(a1), "r"(b0));
}
__device__ __forceinline__ uint32_t movm(uint32_t a) {
    uint32_t d; asm("movmatrix.sync.aligned.m8n8.trans.b16 %0, %1;" : "=r"(d) : "r"(a)); return d;
}

__device__ __forceinline__ void wgmma_n48(float (&d)[24], uint32_t alo, uint32_t ahi, uint32_t blo, uint32_t bhi, int sd) {
    asm volatile("{\n.reg .pred p;\n.reg .b64 da, db;\nsetp.ne.b32 p, %28, 0;\nmov.b64 da, {%24,%25};\nmov.b64 db, {%26,%27};\n"
        "wgmma.mma_async.sync.aligned.m64n48k16.f32.bf16.bf16 {"
        "%0,%1,%2,%3,%4,%5,%6,%7,%8,%9,%10,%11,%12,%13,%14,%15,"
        "%16,%17,%18,%19,%20,%21,%22,%23"
        "}, da, db, p, 1, 1, 0, 1;\n}\n"
        : "+f"(d[0]), "+f"(d[1]), "+f"(d[2]), "+f"(d[3]), "+f"(d[4]), "+f"(d[5]), "+f"(d[6]), "+f"(d[7]),
          "+f"(d[8]), "+f"(d[9]), "+f"(d[10]), "+f"(d[11]), "+f"(d[12]), "+f"(d[13]), "+f"(d[14]), "+f"(d[15]),
          "+f"(d[16]), "+f"(d[17]), "+f"(d[18]), "+f"(d[19]), "+f"(d[20]), "+f"(d[21]), "+f"(d[22]), "+f"(d[23])
        : "r"(alo), "r"(ahi), "r"(blo), "r"(bhi), "r"(sd));
}
__device__ __forceinline__ void wgmma_n128(float (&d)[64], uint32_t alo, uint32_t ahi, uint32_t blo, uint32_t bhi, int sd) {
    asm volatile("{\n.reg .pred p;\n.reg .b64 da, db;\nsetp.ne.b32 p, %68, 0;\nmov.b64 da, {%64,%65};\nmov.b64 db, {%66,%67};\n"
        "wgmma.mma_async.sync.aligned.m64n128k16.f32.bf16.bf16 {"
        "%0,%1,%2,%3,%4,%5,%6,%7,%8,%9,%10,%11,%12,%13,%14,%15,"
        "%16,%17,%18,%19,%20,%21,%22,%23,%24,%25,%26,%27,%28,%29,%30,%31,"
        "%32,%33,%34,%35,%36,%37,%38,%39,%40,%41,%42,%43,%44,%45,%46,%47,"
        "%48,%49,%50,%51,%52,%53,%54,%55,%56,%57,%58,%59,%60,%61,%62,%63"
        "}, da, db, p, 1, 1, 0, 1;\n}\n"
        : "+f"(d[0]), "+f"(d[1]), "+f"(d[2]), "+f"(d[3]), "+f"(d[4]), "+f"(d[5]), "+f"(d[6]), "+f"(d[7]),
          "+f"(d[8]), "+f"(d[9]), "+f"(d[10]), "+f"(d[11]), "+f"(d[12]), "+f"(d[13]), "+f"(d[14]), "+f"(d[15]),
          "+f"(d[16]), "+f"(d[17]), "+f"(d[18]), "+f"(d[19]), "+f"(d[20]), "+f"(d[21]), "+f"(d[22]), "+f"(d[23]),
          "+f"(d[24]), "+f"(d[25]), "+f"(d[26]), "+f"(d[27]), "+f"(d[28]), "+f"(d[29]), "+f"(d[30]), "+f"(d[31]),
          "+f"(d[32]), "+f"(d[33]), "+f"(d[34]), "+f"(d[35]), "+f"(d[36]), "+f"(d[37]), "+f"(d[38]), "+f"(d[39]),
          "+f"(d[40]), "+f"(d[41]), "+f"(d[42]), "+f"(d[43]), "+f"(d[44]), "+f"(d[45]), "+f"(d[46]), "+f"(d[47]),
          "+f"(d[48]), "+f"(d[49]), "+f"(d[50]), "+f"(d[51]), "+f"(d[52]), "+f"(d[53]), "+f"(d[54]), "+f"(d[55]),
          "+f"(d[56]), "+f"(d[57]), "+f"(d[58]), "+f"(d[59]), "+f"(d[60]), "+f"(d[61]), "+f"(d[62]), "+f"(d[63])
        : "r"(alo), "r"(ahi), "r"(blo), "r"(bhi), "r"(sd));
}
__device__ __forceinline__ void wgmma_n160(float (&d)[80], uint32_t alo, uint32_t ahi, uint32_t blo, uint32_t bhi, int sd) {
    asm volatile("{\n.reg .pred p;\n.reg .b64 da, db;\nsetp.ne.b32 p, %84, 0;\nmov.b64 da, {%80,%81};\nmov.b64 db, {%82,%83};\n"
        "wgmma.mma_async.sync.aligned.m64n160k16.f32.bf16.bf16 {"
        "%0,%1,%2,%3,%4,%5,%6,%7,%8,%9,%10,%11,%12,%13,%14,%15,"
        "%16,%17,%18,%19,%20,%21,%22,%23,%24,%25,%26,%27,%28,%29,%30,%31,"
        "%32,%33,%34,%35,%36,%37,%38,%39,%40,%41,%42,%43,%44,%45,%46,%47,"
        "%48,%49,%50,%51,%52,%53,%54,%55,%56,%57,%58,%59,%60,%61,%62,%63,"
        "%64,%65,%66,%67,%68,%69,%70,%71,%72,%73,%74,%75,%76,%77,%78,%79"
        "}, da, db, p, 1, 1, 0, 1;\n}\n"
        : "+f"(d[0]), "+f"(d[1]), "+f"(d[2]), "+f"(d[3]), "+f"(d[4]), "+f"(d[5]), "+f"(d[6]), "+f"(d[7]),
          "+f"(d[8]), "+f"(d[9]), "+f"(d[10]), "+f"(d[11]), "+f"(d[12]), "+f"(d[13]), "+f"(d[14]), "+f"(d[15]),
          "+f"(d[16]), "+f"(d[17]), "+f"(d[18]), "+f"(d[19]), "+f"(d[20]), "+f"(d[21]), "+f"(d[22]), "+f"(d[23]),
          "+f"(d[24]), "+f"(d[25]), "+f"(d[26]), "+f"(d[27]), "+f"(d[28]), "+f"(d[29]), "+f"(d[30]), "+f"(d[31]),
          "+f"(d[32]), "+f"(d[33]), "+f"(d[34]), "+f"(d[35]), "+f"(d[36]), "+f"(d[37]), "+f"(d[38]), "+f"(d[39]),
          "+f"(d[40]), "+f"(d[41]), "+f"(d[42]), "+f"(d[43]), "+f"(d[44]), "+f"(d[45]), "+f"(d[46]), "+f"(d[47]),
          "+f"(d[48]), "+f"(d[49]), "+f"(d[50]), "+f"(d[51]), "+f"(d[52]), "+f"(d[53]), "+f"(d[54]), "+f"(d[55]),
          "+f"(d[56]), "+f"(d[57]), "+f"(d[58]), "+f"(d[59]), "+f"(d[60]), "+f"(d[61]), "+f"(d[62]), "+f"(d[63]),
          "+f"(d[64]), "+f"(d[65]), "+f"(d[66]), "+f"(d[67]), "+f"(d[68]), "+f"(d[69]), "+f"(d[70]), "+f"(d[71]),
          "+f"(d[72]), "+f"(d[73]), "+f"(d[74]), "+f"(d[75]), "+f"(d[76]), "+f"(d[77]), "+f"(d[78]), "+f"(d[79])
        : "r"(alo), "r"(ahi), "r"(blo), "r"(bhi), "r"(sd));
}
__device__ __forceinline__ void wgmma_n192(float (&d)[96], uint32_t alo, uint32_t ahi, uint32_t blo, uint32_t bhi, int sd) {
    asm volatile("{\n.reg .pred p;\n.reg .b64 da, db;\nsetp.ne.b32 p, %100, 0;\nmov.b64 da, {%96,%97};\nmov.b64 db, {%98,%99};\n"
        "wgmma.mma_async.sync.aligned.m64n192k16.f32.bf16.bf16 {"
        "%0,%1,%2,%3,%4,%5,%6,%7,%8,%9,%10,%11,%12,%13,%14,%15,"
        "%16,%17,%18,%19,%20,%21,%22,%23,%24,%25,%26,%27,%28,%29,%30,%31,"
        "%32,%33,%34,%35,%36,%37,%38,%39,%40,%41,%42,%43,%44,%45,%46,%47,"
        "%48,%49,%50,%51,%52,%53,%54,%55,%56,%57,%58,%59,%60,%61,%62,%63,"
        "%64,%65,%66,%67,%68,%69,%70,%71,%72,%73,%74,%75,%76,%77,%78,%79,"
        "%80,%81,%82,%83,%84,%85,%86,%87,%88,%89,%90,%91,%92,%93,%94,%95"
        "}, da, db, p, 1, 1, 0, 1;\n}\n"
        : "+f"(d[0]), "+f"(d[1]), "+f"(d[2]), "+f"(d[3]), "+f"(d[4]), "+f"(d[5]), "+f"(d[6]), "+f"(d[7]),
          "+f"(d[8]), "+f"(d[9]), "+f"(d[10]), "+f"(d[11]), "+f"(d[12]), "+f"(d[13]), "+f"(d[14]), "+f"(d[15]),
          "+f"(d[16]), "+f"(d[17]), "+f"(d[18]), "+f"(d[19]), "+f"(d[20]), "+f"(d[21]), "+f"(d[22]), "+f"(d[23]),
          "+f"(d[24]), "+f"(d[25]), "+f"(d[26]), "+f"(d[27]), "+f"(d[28]), "+f"(d[29]), "+f"(d[30]), "+f"(d[31]),
          "+f"(d[32]), "+f"(d[33]), "+f"(d[34]), "+f"(d[35]), "+f"(d[36]), "+f"(d[37]), "+f"(d[38]), "+f"(d[39]),
          "+f"(d[40]), "+f"(d[41]), "+f"(d[42]), "+f"(d[43]), "+f"(d[44]), "+f"(d[45]), "+f"(d[46]), "+f"(d[47]),
          "+f"(d[48]), "+f"(d[49]), "+f"(d[50]), "+f"(d[51]), "+f"(d[52]), "+f"(d[53]), "+f"(d[54]), "+f"(d[55]),
          "+f"(d[56]), "+f"(d[57]), "+f"(d[58]), "+f"(d[59]), "+f"(d[60]), "+f"(d[61]), "+f"(d[62]), "+f"(d[63]),
          "+f"(d[64]), "+f"(d[65]), "+f"(d[66]), "+f"(d[67]), "+f"(d[68]), "+f"(d[69]), "+f"(d[70]), "+f"(d[71]),
          "+f"(d[72]), "+f"(d[73]), "+f"(d[74]), "+f"(d[75]), "+f"(d[76]), "+f"(d[77]), "+f"(d[78]), "+f"(d[79]),
          "+f"(d[80]), "+f"(d[81]), "+f"(d[82]), "+f"(d[83]), "+f"(d[84]), "+f"(d[85]), "+f"(d[86]), "+f"(d[87]),
          "+f"(d[88]), "+f"(d[89]), "+f"(d[90]), "+f"(d[91]), "+f"(d[92]), "+f"(d[93]), "+f"(d[94]), "+f"(d[95])
        : "r"(alo), "r"(ahi), "r"(blo), "r"(bhi), "r"(sd));
}

constexpr uint32_t HI_128 = 0x40000040u;
constexpr uint32_t HI_32 = 0xC0000010u;
__device__ __forceinline__ constexpr uint32_t lbo(uint32_t bytes) { return (bytes >> 4) << 16; }

struct Ctx {
    uint32_t sb;
    uint32_t bar;
    uint32_t rbar;
    uint32_t a_lo;
    uint32_t b_lo;
    int lane, q, g, w, par;
    float n0, n1, r0, r1;
    float ga0, ga1, gb0, gb1;
};

__device__ __forceinline__ void arrive_both(const Ctx& c, int bar_idx) {
    if (c.lane < 2) mbar_arrive_cluster(c.rbar + bar_idx * 8);
}
__device__ __forceinline__ void arrive_local(const Ctx& c, int bar_idx) {
    __syncwarp();
    if (c.lane == 0) mbar_arrive(c.bar + bar_idx * 8);
}

__device__ __forceinline__ void stsm4(uint32_t addr, uint32_t a, uint32_t b, uint32_t c, uint32_t d) {
    asm volatile("stmatrix.sync.aligned.m8n8.x4.shared.b16 [%0], {%1, %2, %3, %4};" ::"r"(addr), "r"(a), "r"(b), "r"(c), "r"(d) : "memory");
}
__device__ __forceinline__ void tma3_red(const CUtensorMap* m, uint32_t src, int c0, int c1, int c2) {
    asm volatile("cp.reduce.async.bulk.tensor.3d.global.shared::cta.add.tile.bulk_group [%0, {%2, %3, %4}], [%1];"
                 ::"l"(m), "r"(src), "r"(c0), "r"(c1), "r"(c2) : "memory");
}
__device__ __forceinline__ void stg128(__nv_bfloat16* p, uint32_t a, uint32_t b, uint32_t c, uint32_t d) {
    *reinterpret_cast<uint4*>(p) = make_uint4(a, b, c, d);
}

template <int I0, int I1, int N>
__device__ __forceinline__ void row_scale(const Ctx& c, float (&a)[N]) {
#pragma unroll
    for (int i = I0; i < I1; i++) a[i] *= (i & 2) ? c.r1 : c.r0;
}
__device__ __forceinline__ void ln_pack(const Ctx& c, const float* a, int col, uint32_t& lo, uint32_t& hi) {
    float2 cs = lds64(c.sb + SM_CS + (col + 2 * c.q) * 4);
    lo = pack2(fmaf(c.n0, cs.x, a[0]), fmaf(c.n0, cs.y, a[1]));
    hi = pack2(fmaf(c.n1, cs.x, a[2]), fmaf(c.n1, cs.y, a[3]));
}
template <int PART, int G0, int G1>
__device__ __forceinline__ void qkv_pack(const Ctx& c, const float (&a1)[96], const float (&a2)[24], uint32_t (&dst)[20]) {
#pragma unroll
    for (int G = G0; G < G1; G++) {
        if (G < 8) ln_pack(c, &a1[PART * 32 + G * 4], PART * 64 + G * 8, dst[2 * G], dst[2 * G + 1]);
        else ln_pack(c, &a2[PART * 8 + (G - 8) * 4], 192 + PART * 16 + (G - 8) * 8, dst[2 * G], dst[2 * G + 1]);
    }
}

template <int H>
__device__ __forceinline__ void attn_logits(const Ctx& c, bool first, const uint32_t (&qp)[20], const uint32_t (&kp)[20],
                                            const uint32_t (&hk)[10], float (&s)[4]) {
    constexpr int GA = (H == 0) ? 0 : (H == 1) ? 3 : (H == 2) ? 5 : 8;
    constexpr int GS = (H < 2) ? 2 : 7;
    const bool mine = (H & 1) ? (c.q >= 2) : (c.q < 2);
    const uint32_t qs0 = mine ? qp[2 * GS] : 0u, qs1 = mine ? qp[2 * GS + 1] : 0u;
    float sP[4] = {0.f, 0.f, 0.f, 0.f}, sL[4] = {0.f, 0.f, 0.f, 0.f}, sU[4] = {0.f, 0.f, 0.f, 0.f};
    mma16(sP, qp[2 * GA], qp[2 * GA + 1], qp[2 * GA + 2], qp[2 * GA + 3], hk[GA], hk[GA + 1]);
    mma16(sL, qp[2 * GA], qp[2 * GA + 1], qp[2 * GA + 2], qp[2 * GA + 3], kp[2 * GA], kp[2 * GA + 2]);
    mma16(sU, qp[2 * GA], qp[2 * GA + 1], qp[2 * GA + 2], qp[2 * GA + 3], kp[2 * GA + 1], kp[2 * GA + 3]);
    mma8(sP, qs0, qs1, hk[GS]);
    mma8(sL, qs0, qs1, kp[2 * GS]);
    mma8(sU, qs0, qs1, kp[2 * GS + 1]);
    const bool gt0 = 2 * c.q > c.g, gt1 = 2 * c.q + 1 > c.g;
    const float ninf = __int_as_float(0xff800000);
    s[0] = gt0 ? (first ? ninf : sP[0]) : sL[0];
    s[1] = gt1 ? (first ? ninf : sP[1]) : sL[1];
    s[2] = gt0 ? sL[2] : sU[2];
    s[3] = gt1 ? sL[3] : sU[3];
}
constexpr float kScale = 0.22360679774997896f * 1.4426950408889634f;
__device__ __forceinline__ void attn_max(const float (&s)[4][4], float (&m)[4][2]) {
#pragma unroll
    for (int h = 0; h < 4; h++) { m[h][0] = fmaxf(s[h][0], s[h][1]); m[h][1] = fmaxf(s[h][2], s[h][3]); }
#pragma unroll
    for (int o = 1; o < 4; o <<= 1) {
#pragma unroll
        for (int h = 0; h < 4; h++) {
            m[h][0] = fmaxf(m[h][0], __shfl_xor_sync(0xffffffffu, m[h][0], o));
            m[h][1] = fmaxf(m[h][1], __shfl_xor_sync(0xffffffffu, m[h][1], o));
        }
    }
}
__device__ __forceinline__ void attn_exp(float (&s)[4][4], float (&m)[4][2]) {
#pragma unroll
    for (int h = 0; h < 4; h++) {
        const float m0 = m[h][0] * -kScale, m1 = m[h][1] * -kScale;
        s[h][0] = ex2(fmaf(s[h][0], kScale, m0)); s[h][1] = ex2(fmaf(s[h][1], kScale, m0));
        s[h][2] = ex2(fmaf(s[h][2], kScale, m1)); s[h][3] = ex2(fmaf(s[h][3], kScale, m1));
        m[h][0] = s[h][0] + s[h][1]; m[h][1] = s[h][2] + s[h][3];
    }
}
__device__ __forceinline__ void attn_sum(float (&m)[4][2]) {
#pragma unroll
    for (int o = 1; o < 4; o <<= 1) {
#pragma unroll
        for (int h = 0; h < 4; h++) {
            m[h][0] += __shfl_xor_sync(0xffffffffu, m[h][0], o);
            m[h][1] += __shfl_xor_sync(0xffffffffu, m[h][1], o);
        }
    }
#pragma unroll
    for (int h = 0; h < 4; h++) { m[h][0] = rcp(m[h][0]); m[h][1] = rcp(m[h][1]); }
}
__device__ __forceinline__ void attn_probs(const Ctx& c, const float (&s)[4][4], const float (&m)[4][2], uint32_t (&p)[4][4]) {
    const uint32_t mk = ((2 * c.q > c.g) ? 0x0000ffffu : 0u) | ((2 * c.q + 1 > c.g) ? 0xffff0000u : 0u);
#pragma unroll
    for (int h = 0; h < 4; h++) {
        const uint32_t lo = pack2(s[h][0] * m[h][0], s[h][1] * m[h][0]), hi = pack2(s[h][2] * m[h][1], s[h][3] * m[h][1]);
        p[h][0] = lo & mk; p[h][1] = lo & ~mk; p[h][2] = hi & mk; p[h][3] = hi & ~mk;
    }
}
template <int H>
__device__ __forceinline__ void attn_pv(const Ctx& c, const uint32_t (&p)[4], const uint32_t (&vp)[20], const uint32_t (&hv)[10], uint32_t (&op)[20]) {
    constexpr int GA = (H == 0) ? 0 : (H == 1) ? 3 : (H == 2) ? 5 : 8;
    constexpr int GS = (H < 2) ? 2 : 7;
    const bool mine = (H & 1) ? (c.q >= 2) : (c.q < 2);
#pragma unroll
    for (int t = 0; t < 3; t++) {
        const int G = (t < 2) ? GA + t : GS;
        float o[4] = {0.f, 0.f, 0.f, 0.f};
        mma16(o, p[0], 0u, p[1], p[2], movm(hv[G]), movm(vp[2 * G]));
        mma8(o, 0u, p[3], movm(vp[2 * G + 1]));
        const uint32_t lo = pack2(o[0], o[1]), hi = pack2(o[2], o[3]);
        if (t < 2 || (H & 1) == 0) { op[2 * G] = lo; op[2 * G + 1] = hi; }
        else { op[2 * G] = mine ? lo : op[2 * G]; op[2 * G + 1] = mine ? hi : op[2 * G + 1]; }
    }
}

__device__ __forceinline__ void swiglu_group(const Ctx& c, const float (&acc)[64], int G, uint32_t& lo, uint32_t& hi) {
    float h[4];
#pragma unroll
    for (int e = 0; e < 4; e++) {
        const float gate = acc[4 * G + e], up = acc[32 + 4 * G + e];
        const float ga = (e < 2) ? c.ga0 : c.ga1, gb = (e < 2) ? c.gb0 : c.gb1;
        h[e] = (gate * up) * fmaf(tanh_fast(gate * ga), gb, gb);
    }
    lo = pack2(h[0], h[1]);
    hi = pack2(h[2], h[3]);
}
template <int G0, int G1>
__device__ __forceinline__ void swiglu_groups(const Ctx& c, const float (&acc)[64], uint32_t (&hp)[8], __nv_bfloat16* hrow) {
#pragma unroll
    for (int G = G0; G < G1; G++) {
        swiglu_group(c, acc, G, hp[G & 3], hp[4 + (G & 3)]);
        if ((G & 3) == 3) {
            stg128(hrow + 32 * (G >> 2), hp[0], hp[1], hp[2], hp[3]);
            stg128(hrow + 8 * kActLd + 32 * (G >> 2), hp[4], hp[5], hp[6], hp[7]);
        }
    }
}

template <int N>
__device__ __forceinline__ void f_issue(const Ctx& c, float (&acc)[64]) {
    constexpr int S = (N - 20) % 10, SLOT = N & 3;
    if (threadIdx.x < 32) TRACE(192 + N);
    if (N < 30) mbar_wait(c.bar + (B_XN + S) * 8, 0);
    mbar_wait(c.bar + (B_RFULL + SLOT) * 8, (N >> 2) & 1);
    if (threadIdx.x < 32) TRACE(64 + N);
    wg_fence();
#pragma unroll
    for (int kk = 0; kk < 4; kk++)
        wgmma_n128(acc, c.a_lo + S * 1024 + kk * 2, HI_128, c.b_lo + lbo(8192) + SLOT * 1024 + kk * 128, HI_128, (S | kk) != 0);
    wg_commit();
    wg_wait<1>();
    if (N - 1 <= 45) arrive_both(c, (N - 1 < 20 ? B_REMPTYQ : B_REMPTYF) + ((N - 1) & 3));
    if (N == 20 && c.lane == 0) mbar_arrive(c.bar + (B_XFREE + 9) * 8);
    if (N == 43) arrive_both(c, B_GEMPTY + 0);
    if (N == 45) arrive_both(c, B_GEMPTY + 1);
    if (N == 48) arrive_both(c, B_GEMPTY + 2);
}

__device__ __forceinline__ void g_issue(const Ctx& c, float (&acc)[80], int slot, int parity, bool first, int t) {
    if (threadIdx.x < 32) TRACE(250 + t);
    mbar_wait(c.bar + (B_GFULL + slot) * 8, parity);
    if (threadIdx.x < 32) TRACE(120 + t);
    wg_fence();
    const uint32_t st = ((c.sb & 0x3FFFF) >> 4) + slot * (G_STAGE >> 4);
    const uint32_t alo = st + c.par * 512 + lbo(16), blo = st + 1024 + lbo(4096);
#pragma unroll
    for (int kk = 0; kk < 4; kk++)
        wgmma_n160(acc, alo + kk * 2, HI_128, blo + (kk >> 1) * 768 + (kk & 1) * 128, HI_128, !(first && kk == 0));
    wg_commit();
}

template <int N>
__device__ __forceinline__ void halve(float (&acc)[16], int lane) {
    const bool up = lane & (2 * N);
#pragma unroll
    for (int e = 0; e < N; e++) {
        const float lo = acc[e], hi = acc[e + N];
        const float send = up ? lo : hi, keep = up ? hi : lo;
        acc[e] = keep + __shfl_xor_sync(0xffffffffu, send, 2 * N);
    }
}

__device__ __forceinline__ void prefetch_stage(int m, int b, const __nv_bfloat16* wqkv, const __nv_bfloat16* w1, const __nv_bfloat16* w3) {
    if (m < 20) prefetch_l2(wqkv + (size_t)(32 * m + (b & 31)) * 1920 + (b >> 5) * 480, 960);
    else if (m < 50) {
        const int f = (m - 20) / 10, s = (m - 20) % 10;
        prefetch_l2(((b >> 6) ? w3 : w1) + (size_t)(64 * s + (b & 63)) * kF + 512 * f, 1024);
    }
}

}

__global__ void __cluster_dims__(2, 1, 1) __launch_bounds__(384, 1)
fused_block_kernel(const __grid_constant__ Maps maps, const __nv_bfloat16* __restrict__ x, const __nv_bfloat16* __restrict__ wqkv,
                   const __nv_bfloat16* __restrict__ w1, const __nv_bfloat16* __restrict__ w3,
                   const __nv_bfloat16* __restrict__ wo, const __nv_bfloat16* __restrict__ w2, __nv_bfloat16* __restrict__ out) {
    extern __shared__ __align__(1024) uint8_t smem_raw[];
    const uint32_t sb = smem_u32(smem_raw);
    const int warp = __shfl_sync(0xffffffffu, threadIdx.x >> 5, 0);
    const int lane = threadIdx.x & 31;
    uint32_t rank;
    asm("mov.u32 %0, %%cluster_ctarank;" : "=r"(rank));
    const int b = blockIdx.x;
    const int pair = b >> 1;
    const int slot = pair & 7;
    const int tile = (pair >> 3) * 2 + rank;
    const int jj = slot & 3;
    const int half = slot >> 2;

    unsigned cnt0 = 0;
    if (threadIdx.x == 0) TRACE(0);
    if (warp == 8) TRACEG(62);
    if (warp >= 9) {
        cnt0 = ld_relaxed(&g_cntO[tile * 32]);
        if (warp == 9 && lane == 0) { prefetch_map(&maps.x); prefetch_map(&maps.wq); prefetch_map(&maps.wqr); }
    }
    if (elect_one()) {
#pragma unroll 1
        for (int i = warp; i < B_COUNT; i += 12) {
            uint32_t cnt = 1;
            if (i >= B_REMPTYQ && i < B_REMPTYF) cnt = 18;
            else if ((i >= B_REMPTYF && i < B_GFULL) || (i >= B_GEMPTY && i < B_CS)) cnt = 16;
            else if (i == B_HALOW) cnt = 2;
            else if (i == B_HALOR || i == B_HALOR + 1) cnt = 5;
            else if (i == B_WDONE + 1) cnt = 9;
            else if (i >= B_WDONE && i < B_FLAG) cnt = 8;
            else if (i >= B_XFREE && i < B_XN) cnt = 8;
            else if (i >= B_XN) cnt = 2;
            mbar_init(sb + SM_BAR + i * 8, cnt);
        }
        asm volatile("fence.mbarrier_init.release.cluster;" ::: "memory");
    }
    if (warp == 8) TRACE(22);
    __syncthreads();
    if (warp == 8) TRACE(23);
    asm volatile("barrier.cluster.arrive.relaxed.aligned;" ::: "memory");
    if (warp == 8) {
        if (elect_one()) {
            mbar_expect_tx(sb + SM_BAR + B_XFULL * 8, 16384);
            tma3(sb + SM_X, &maps.x, 0, tile * 64, 0, sb + SM_BAR + B_XFULL * 8);
        }
        __syncwarp();
    }
    asm volatile("barrier.cluster.wait.aligned;" ::: "memory");
    if (warp == 8) TRACE(24);

    if (warp >= 8) {
        asm volatile("setmaxnreg.dec.sync.aligned.u32 56;");
        const uint32_t bar = launder(sb + SM_BAR);
        if (warp == 8) {
            const uint32_t ring = launder(sb + SM_RING);
#pragma unroll 1
            for (int n = 0; n < 20; n++) {
                const int s = n & 3;
                if (n >= 4) mbar_wait(bar + (B_REMPTYQ + s) * 8, ((n >> 2) - 1) & 1);
                const int c = (n == 1) ? 1 : (n == 3) ? 2 : (n >= 4 && n <= 16 && !(n & 1)) ? n / 2 + 1 : 0;
                if (elect_one()) {
                    mbar_expect_tx(bar + (B_RFULL + s) * 8, 15360);
                    tma3_mc(ring + s * 16384 + rank * 6144, &maps.wq, 80 * slot, 32 * n + 16 * rank, 0, bar + (B_RFULL + s) * 8);
                    tma3_mc(ring + s * 16384 + 12288 + rank * 1536, &maps.wqr, 80 * slot + 64, 32 * n + 16 * rank, 0, bar + (B_RFULL + s) * 8);
                    if (c > 0) {
                        mbar_expect_tx(bar + (B_XFULL + c) * 8, 16384);
                        tma3(sb + SM_X + c * 16384, &maps.x, c * 64, tile * 64, 0, bar + (B_XFULL + c) * 8);
                    }
                    if (n == 3) { for (int m = 4; m < 3 + PF_DIST; m++) prefetch_stage(m, b, wqkv, w1, w3); }
                    if (n >= 3) prefetch_stage(n + PF_DIST, b, wqkv, w1, w3);
                    if (n == 8) { prefetch_map(&maps.w1); prefetch_map(&maps.w3); }
                }
                if (n == 0) TRACE(1);
            }
            const CUtensorMap* mf = rank ? &maps.w3 : &maps.w1;
            {
                int col = 64 * slot, k = 0;
#pragma unroll 1
                for (int n = 20; n < 50; n++) {
                    const int s = n & 3;
                    if (n < 24) mbar_wait(bar + (B_REMPTYQ + s) * 8, ((n >> 2) - 1) & 1);
                    else mbar_wait(bar + (B_REMPTYF + s) * 8, ((n - 24) >> 2) & 1);
                    if (elect_one()) {
                        mbar_expect_tx(bar + (B_RFULL + s) * 8, 16384);
                        tma2_mc(ring + s * 16384 + rank * 8192, mf, col, k, bar + (B_RFULL + s) * 8);
                        prefetch_stage(n + PF_DIST, b, wqkv, w1, w3);
                        if (n == 26) prefetch_l2(wo + (size_t)b * 5 * kD, 5 * kD * 2);
                        if (n == 28) prefetch_l2(w2 + (size_t)b * 12 * kD, 12 * kD * 2);
                        if (n == 32) {
                            prefetch_map(&maps.act); prefetch_map(&maps.wo2); prefetch_map(&maps.wo1); prefetch_map(&maps.w22); prefetch_map(&maps.w21);
                            prefetch_map(&maps.o64); prefetch_map(&maps.o32);
                        }
                    }
                    k += 64;
                    if (k == 640) { k = 0; col += 512; }
                }
            }
            TRACE(2);
            int s = 0, ph = 0;
            const int no = half ? 10 - NO0 : NO0, o0 = half ? NO0 : 0;
#pragma unroll 1
            for (int t = 0; t < 12 + no; t++) {
                const int kc = (t < 4) ? 10 + 4 * half + t : (t < 4 + no) ? o0 + t - 4 : (t < 8 + no) ? 14 + 4 * half + t - no : 18 + 4 * half + t - no;
                const int flag = (t == 0) ? 0 : (t == 4) ? 1 : (t == 4 + no) ? 2 : (t == 8 + no) ? 3 : -1;
                mbar_wait(bar + (B_GEMPTY + s) * 8, ph);
                if (flag >= 0) mbar_wait(bar + (B_FLAG + flag) * 8, 0);
                if (elect_one()) {
                    if (flag >= 0) fence_async_global();
                    const uint32_t st = sb + s * G_STAGE, fb = bar + (B_GFULL + s) * 8;
                    const bool isO = kc < 10;
                    const int a0 = ((isO ? kc : kc - 10) * 2 + rank) * 4;
                    mbar_expect_tx(fb, 16384 + 20480);
                    tma5_mc(st + 16384 + rank * 12288, isO ? &maps.wo2 : &maps.w22, 160 * jj, a0, fb);
                    tma4_mc(st + 16384 + rank * 12288 + 8192, isO ? &maps.wo1 : &maps.w21, 160 * jj + 128, a0, fb);
                    tma2(st, &maps.act, kc * 64, tile * 128, fb);
                }
                if (++s == 5) { s = 0; ph ^= 1; }
            }
            TRACE(3);
        } else {
            const int a = warp - 9;
            const unsigned tag = cnt0 / 8 + 1;
            const uint32_t rbar = mapa(bar, lane & 1);
            if (a == 0) {
                const int pc = 2 * tile, h = lane >> 4, kr = lane & 15;
                uint32_t o0, o1;
                if (pc < 24) {
                    o0 = h * 6144 + (pc >> 3) * 2048 + kr * 128 + (((pc & 7) ^ (kr & 7)) << 4);
                    o1 = o0 ^ 16;
                } else {
                    o0 = 12288 + h * 1536 + ((pc - 24) >> 1) * 512 + kr * 32 + (((kr >> 2) & 1) << 4);
                    o1 = o0 ^ 16;
                }
                float acc[16];
#pragma unroll
                for (int e = 0; e < 16; e++) acc[e] = 0.f;
#pragma unroll 1
                for (int n = 0; n < 20; n++) {
                    const int s = n & 3;
                    mbar_wait(bar + (B_RFULL + s) * 8, (n >> 2) & 1);
                    if (tile < 15) {
                        const uint4 v0 = lds128(sb + SM_RING + s * 16384 + o0), v1 = lds128(sb + SM_RING + s * 16384 + o1);
                        acc[0] += bf_lo(v0.x); acc[1] += bf_hi(v0.x); acc[2] += bf_lo(v0.y); acc[3] += bf_hi(v0.y);
                        acc[4] += bf_lo(v0.z); acc[5] += bf_hi(v0.z); acc[6] += bf_lo(v0.w); acc[7] += bf_hi(v0.w);
                        acc[8] += bf_lo(v1.x); acc[9] += bf_hi(v1.x); acc[10] += bf_lo(v1.y); acc[11] += bf_hi(v1.y);
                        acc[12] += bf_lo(v1.z); acc[13] += bf_hi(v1.z); acc[14] += bf_lo(v1.w); acc[15] += bf_hi(v1.w);
                    }
                    __syncwarp();
                    if (lane < 2) mbar_arrive_cluster(rbar + (B_REMPTYQ + s) * 8);
                }
                TRACE(25);
                if (tile < 15) {
                    halve<8>(acc, lane); halve<4>(acc, lane); halve<2>(acc, lane); halve<1>(acc, lane);
                    acc[0] += __shfl_xor_sync(0xffffffffu, acc[0], 1);
                    if (!(lane & 1)) st_tag(&g_cs[slot * 256 + 16 * tile + (lane >> 1)], tagged(tag, acc[0]));
                }
                {
                    unsigned long long v[8];
                    int it = 0;
#pragma unroll 1
                    while (true) {
                        bool ok = true;
#pragma unroll
                        for (int u = 0; u < 4; u++) {
                            const int n2 = lane + 32 * u;
                            if (n2 < 120) {
                                ld_tag2(&g_cs[slot * 256 + 2 * n2], v[2 * u], v[2 * u + 1]);
                                ok = ok && (uint32_t)(v[2 * u] >> 32) == tag && (uint32_t)(v[2 * u + 1] >> 32) == tag;
                            }
                        }
                        if (__all_sync(0xffffffffu, ok) || ++it > (1 << 15)) break;
                    }
#pragma unroll
                    for (int u = 0; u < 4; u++) {
                        const int n2 = lane + 32 * u;
                        if (n2 < 120) asm volatile("st.shared.v2.u32 [%0], {%1,%2};" ::"r"(sb + SM_CS + n2 * 8), "r"((uint32_t)v[2 * u]), "r"((uint32_t)v[2 * u + 1]) : "memory");
                    }
                    __syncwarp();
                    if (lane == 0) mbar_arrive(bar + B_CS * 8);
                }
                TRACE(5);
#pragma unroll 1
                for (int kb = 0; kb < 5; kb++) {
                    uint4 v[8];
#pragma unroll
                    for (int u = 0; u < 8; u++) {
                        const int idx = lane + 32 * (8 * kb + u), row = (idx * 6554) >> 16;
                        const int off = (tile * 128 + row) * kD + 80 * slot + 8 * (idx - 10 * row);
                        asm volatile("ld.global.nc.v4.u32 {%0,%1,%2,%3}, [%4];" : "=r"(v[u].x), "=r"(v[u].y), "=r"(v[u].z), "=r"(v[u].w) : "l"(x + off));
                    }
#pragma unroll
                    for (int u = 0; u < 8; u++) {
                        const int idx = lane + 32 * (8 * kb + u), row = (idx * 6554) >> 16;
                        const int off = (tile * 128 + row) * kD + 80 * slot + 8 * (idx - 10 * row);
                        *reinterpret_cast<uint4*>(out + off) = v[u];
                    }
                }
                __syncwarp();
                if (lane == 0) mbar_arrive(bar + (B_WDONE + 1) * 8);
                TRACE(7);
            } else {
#pragma unroll 1
                for (int bt = 0; bt < 4; bt++) {
                    const int tok = tile * 128 + 16 * slot + 8 * (a - 1) + 2 * bt + (lane >> 4);
                    mbar_wait(bar + (B_XFULL + 1 + bt) * 8, 0);
                    const uint4* xr = reinterpret_cast<const uint4*>(x + (size_t)tok * kD) + (lane & 15);
                    uint4 v[5];
#pragma unroll
                    for (int u = 0; u < 5; u++)
                        asm volatile("ld.global.nc.v4.u32 {%0,%1,%2,%3}, [%4];" : "=r"(v[u].x), "=r"(v[u].y), "=r"(v[u].z), "=r"(v[u].w) : "l"(xr + 16 * u));
                    const float x0 = __shfl_sync(0xffffffffu, bf_lo(v[0].x), lane & 16);
                    float s4[4] = {0.f, 0.f, 0.f, 0.f}, q4[4] = {0.f, 0.f, 0.f, 0.f};
#pragma unroll
                    for (int u = 0; u < 5; u++) {
                        const uint32_t wv[4] = {v[u].x, v[u].y, v[u].z, v[u].w};
#pragma unroll
                        for (int e = 0; e < 4; e++) {
                            const float d0 = bf_lo(wv[e]) - x0, d1 = bf_hi(wv[e]) - x0;
                            s4[e] += d0; q4[e] = fmaf(d0, d0, q4[e]);
                            s4[e] += d1; q4[e] = fmaf(d1, d1, q4[e]);
                        }
                    }
                    float s = (s4[0] + s4[1]) + (s4[2] + s4[3]), ss = (q4[0] + q4[1]) + (q4[2] + q4[3]);
#pragma unroll
                    for (int o = 1; o < 16; o <<= 1) { s += __shfl_xor_sync(0xffffffffu, s, o); ss += __shfl_xor_sync(0xffffffffu, ss, o); }
                    if ((lane & 15) == 0) {
                        const float dm = s * (1.f / kD), var = fmaxf(ss * (1.f / kD) - dm * dm, 0.f);
                        st_tag2(&g_stats[(size_t)tok * 2], tagged(tag, 1.f / sqrtf(var + 1e-5f)), tagged(tag, x0 + dm));
                    }
                }
                if (a == 1) TRACE(26);
                if (a == 1) {
                    unsigned long long v[8];
                    int it = 0;
#pragma unroll 1
                    while (true) {
                        bool ok = true;
#pragma unroll
                        for (int u = 0; u < 4; u++) {
                            const int rho = lane + 32 * u;
                            ld_tag2(&g_stats[(size_t)(tile * 128 + 2 * (rho & 63) + (rho >> 6)) * 2], v[2 * u], v[2 * u + 1]);
                            ok = ok && (uint32_t)(v[2 * u] >> 32) == tag && (uint32_t)(v[2 * u + 1] >> 32) == tag;
                        }
                        if (__all_sync(0xffffffffu, ok) || ++it > (1 << 15)) break;
                    }
#pragma unroll
                    for (int u = 0; u < 4; u++) {
                        const int rho = lane + 32 * u;
                        const float r = __uint_as_float((uint32_t)v[2 * u]), m = __uint_as_float((uint32_t)v[2 * u + 1]);
                        asm volatile("st.shared.v2.f32 [%0], {%1,%2};" ::"r"(sb + SM_ST + rho * 8), "f"(r), "f"(-m * r) : "memory");
                        asm volatile("st.shared.u32 [%0], %1;" ::"r"(sb + SM_NM + rho * 4), "r"(pack2(-m, -m)) : "memory");
                    }
                    __syncwarp();
                    if (lane == 0) mbar_arrive(bar + B_ST * 8);
                    TRACE(6);
                }
                mbar_wait(bar + B_ST * 8, 0);
                {
                    const int t64 = (a - 1) * 32 + lane;
                    uint32_t nm[16];
#pragma unroll
                    for (int k = 0; k < 16; k++) nm[k] = lds32(sb + SM_NM + ((t64 >> 3) + 8 * k) * 4);
#pragma unroll 1
                    for (int c = 0; c < 10; c++) {
                        const uint32_t base = sb + SM_X + c * 16384 + t64 * 16;
                        mbar_wait(bar + (B_XFREE + c) * 8, 0);
                        if (a == 1) TRACE(140 + c);
#pragma unroll
                        for (int kb = 0; kb < 4; kb++) {
                            uint4 v[4];
#pragma unroll
                            for (int u = 0; u < 4; u++) v[u] = lds128(base + (4 * kb + u) * 1024);
#pragma unroll
                            for (int u = 0; u < 4; u++) {
                                const uint32_t m = nm[4 * kb + u];
                                sts128(base + (4 * kb + u) * 1024, make_uint4(badd2(v[u].x, m), badd2(v[u].y, m), badd2(v[u].z, m), badd2(v[u].w, m)));
                            }
                        }
                        if (a == 1) TRACE(150 + c);
                        asm volatile("fence.proxy.async.shared::cta;" ::: "memory");
                        __syncwarp();
                        if (lane == 0) mbar_arrive(bar + (B_XN + c) * 8);
                    }
                }
                if (a == 1) {
                    TRACE(4);
                    mbar_wait(bar + B_HALOW * 8, 0);
                    if (lane == 0) {
                        if (tile < 15) { fence_gpu(); st_relaxed(&g_flagHalo[(tile * 8 + slot) * 32], tag); }
                        if (tile > 0) poll_ge(&g_flagHalo[((tile - 1) * 8 + slot) * 32], tag);
                        mbar_arrive(bar + B_HALOR * 8);
                        mbar_arrive(bar + (B_HALOR + 1) * 8);
                        const unsigned tgt = tag * 8;
                        poll_ge(&g_cntH[(tile * 3 + 0) * 32], tgt);
                        mbar_arrive(bar + (B_FLAG + 0) * 8);
                        poll_ge(&g_cntO[tile * 32], tgt);
                        mbar_arrive(bar + (B_FLAG + 1) * 8);
                        poll_ge(&g_cntH[(tile * 3 + 1) * 32], tgt);
                        mbar_arrive(bar + (B_FLAG + 2) * 8);
                        poll_ge(&g_cntH[(tile * 3 + 2) * 32], tgt);
                        mbar_arrive(bar + (B_FLAG + 3) * 8);
                    }
                } else {
#pragma unroll 1
                    for (int r = 0; r < 4; r++) {
                        mbar_wait(bar + (B_WDONE + r) * 8, 0);
                        unsigned* cnt = (r == 1) ? &g_cntO[tile * 32] : &g_cntH[(tile * 3 + (r == 0 ? 0 : r - 1)) * 32];
                        if (lane == 0) { fence_async_global(); fence_gpu(); red_add(cnt, 1); }
                    }
                }
            }
        }
    } else {
        asm volatile("setmaxnreg.inc.sync.aligned.u32 224;");
        Ctx c;
        c.sb = sb;
        c.bar = sb + SM_BAR;
        c.lane = lane; c.q = lane & 3; c.g = lane >> 2; c.w = warp & 3; c.par = warp >> 2;
        c.rbar = mapa(c.bar, lane & 1);
        c.a_lo = ((sb & 0x3FFFF) >> 4) + c.par * 512 + lbo(16);
        c.b_lo = ((sb + SM_RING) & 0x3FFFF) >> 4;
        const int idx0 = c.w * 16 + c.g;
        __nv_bfloat16* actrow = g_act + (size_t)(tile * 128 + c.par * 64 + idx0) * kActLd + 8 * c.q;

        float q1[96], q2[24];
#pragma unroll
        for (int n = 0; n < 20; n++) {
            if (warp == 0) TRACE(192 + n);
            if ((n & 1) == 0) mbar_wait(c.bar + (B_XFULL + n / 2) * 8, 0);
            mbar_wait(c.bar + (B_RFULL + (n & 3)) * 8, (n >> 2) & 1);
            if (n == 0 && c.w == 0) TRACE(8 + c.par);
            if (warp == 0) TRACE(64 + n);
            wg_fence();
#pragma unroll
            for (int h = 0; h < 2; h++) {
                const uint32_t alo = c.a_lo + (n >> 1) * 1024 + ((n & 1) * 2 + h) * 2;
                wgmma_n192(q1, alo, HI_128, c.b_lo + lbo(2048) + (n & 3) * 1024 + h * 384, HI_128, (n | h) != 0);
                wgmma_n48(q2, alo, HI_128, c.b_lo + lbo(512) + (n & 3) * 1024 + 768 + h * 96, HI_32, (n | h) != 0);
            }
            wg_commit();
            wg_wait<1>();
            if (n > 0) arrive_both(c, B_REMPTYQ + ((n - 1) & 3));
            if (n >= 2 && (n & 1) == 0 && lane == 0) mbar_arrive(c.bar + (B_XFREE + n / 2 - 1) * 8);
        }
        if (c.w == 0) TRACE(10 + c.par);

        float accA[64], accB[64];
        uint32_t qp[20], kp[20], vp[20], hk[10], hv[10], op[20], hp[8];
        const bool first = (tile == 0) && (c.w == 0);
        f_issue<20>(c, accA);
        {
            mbar_wait(c.bar + B_ST * 8, 0);
            const float2 s0 = lds64(sb + SM_ST + (c.par * 64 + idx0) * 8), s1 = lds64(sb + SM_ST + (c.par * 64 + idx0 + 8) * 8);
            c.r0 = s0.x; c.n0 = s0.y; c.r1 = s1.x; c.n1 = s1.y;
        }
        f_issue<21>(c, accA); row_scale<0, 40>(c, q1);
        f_issue<22>(c, accA); row_scale<40, 80>(c, q1);
        f_issue<23>(c, accA); row_scale<80, 96>(c, q1); row_scale<0, 24>(c, q2);
        f_issue<24>(c, accA); mbar_wait(c.bar + B_CS * 8, 0); qkv_pack<1, 0, 5>(c, q1, q2, kp);
        f_issue<25>(c, accA); qkv_pack<1, 5, 10>(c, q1, q2, kp);
        f_issue<26>(c, accA); qkv_pack<2, 0, 5>(c, q1, q2, vp);
        f_issue<27>(c, accA); qkv_pack<2, 5, 10>(c, q1, q2, vp);
        {
            const int dt = (c.w == 3) ? tile + 1 : tile, dw = (c.w + 1) & 3;
            if (dt < 16) {
                uint4* hq = g_halo + (size_t)(((dt * 8 + slot) * 2 + c.par) * 4 + dw) * 160 + lane;
                hq[0] = make_uint4(kp[1], kp[3], kp[5], kp[7]);
                hq[32] = make_uint4(kp[9], kp[11], kp[13], kp[15]);
                hq[64] = make_uint4(kp[17], kp[19], vp[1], vp[3]);
                hq[96] = make_uint4(vp[5], vp[7], vp[9], vp[11]);
                hq[128] = make_uint4(vp[13], vp[15], vp[17], vp[19]);
            }
            __syncwarp();
            if (lane == 0) {
                mbar_arrive(c.bar + (B_HALOR + c.par) * 8);
                if (c.w == 3) mbar_arrive(c.bar + B_HALOW * 8);
            }
        }
        f_issue<28>(c, accA); qkv_pack<0, 0, 5>(c, q1, q2, qp);
        f_issue<29>(c, accA); qkv_pack<0, 5, 10>(c, q1, q2, qp);
        c.ga0 = 0.5f * c.r0; c.ga1 = 0.5f * c.r1; c.gb0 = c.ga0 * c.r0; c.gb1 = c.ga1 * c.r1;
        if (c.w == 0) TRACE(12 + c.par);

        __nv_bfloat16* hrow0 = actrow + kD + 64 * slot;
        f_issue<30>(c, accB); swiglu_groups<0, 2>(c, accA, hp, hrow0);
        f_issue<31>(c, accB); swiglu_groups<2, 4>(c, accA, hp, hrow0);
        f_issue<32>(c, accB); swiglu_groups<4, 6>(c, accA, hp, hrow0);
        f_issue<33>(c, accB); swiglu_groups<6, 8>(c, accA, hp, hrow0);
        arrive_local(c, B_WDONE + 0);
        f_issue<34>(c, accB);
        {
            mbar_wait(c.bar + (B_HALOR + c.par) * 8, 0);
            const uint4* hq = g_halo + (size_t)(((tile * 8 + slot) * 2 + c.par) * 4 + c.w) * 160 + lane;
            uint4 t0 = make_uint4(0, 0, 0, 0), t1 = t0, t2 = t0, t3 = t0, t4 = t0;
            if (!first) { t0 = __ldcg(hq); t1 = __ldcg(hq + 32); t2 = __ldcg(hq + 64); t3 = __ldcg(hq + 96); t4 = __ldcg(hq + 128); }
            hk[0] = t0.x; hk[1] = t0.y; hk[2] = t0.z; hk[3] = t0.w; hk[4] = t1.x; hk[5] = t1.y; hk[6] = t1.z; hk[7] = t1.w;
            hk[8] = t2.x; hk[9] = t2.y; hv[0] = t2.z; hv[1] = t2.w; hv[2] = t3.x; hv[3] = t3.y; hv[4] = t3.z; hv[5] = t3.w;
            hv[6] = t4.x; hv[7] = t4.y; hv[8] = t4.z; hv[9] = t4.w;
        }
        float sc[4][4], mx[4][2];
        uint32_t pr[4][4];
        f_issue<35>(c, accB);
        attn_logits<0>(c, first, qp, kp, hk, sc[0]); attn_logits<1>(c, first, qp, kp, hk, sc[1]);
        attn_logits<2>(c, first, qp, kp, hk, sc[2]); attn_logits<3>(c, first, qp, kp, hk, sc[3]);
        f_issue<36>(c, accB); attn_max(sc, mx);
        f_issue<37>(c, accB); attn_exp(sc, mx);
        f_issue<38>(c, accB); attn_sum(mx);
        f_issue<39>(c, accB); attn_probs(c, sc, mx, pr);
        if (c.w == 0) TRACE(14 + c.par);

        f_issue<40>(c, accA); attn_pv<0>(c, pr[0], vp, hv, op); attn_pv<1>(c, pr[1], vp, hv, op);
        f_issue<41>(c, accA); attn_pv<2>(c, pr[2], vp, hv, op); attn_pv<3>(c, pr[3], vp, hv, op);
        f_issue<42>(c, accA);
        {
            __nv_bfloat16* orow = actrow + 160 * (slot >> 1);
            if ((slot & 1) == 0) {
                stg128(orow, op[0], op[2], op[4], op[6]);
                stg128(orow + 8 * kActLd, op[1], op[3], op[5], op[7]);
                stg128(orow + 32, op[8], op[10], op[12], op[14]);
                stg128(orow + 8 * kActLd + 32, op[9], op[11], op[13], op[15]);
                *reinterpret_cast<uint2*>(orow + 64) = make_uint2(op[16], op[18]);
                *reinterpret_cast<uint2*>(orow + 8 * kActLd + 64) = make_uint2(op[17], op[19]);
            } else {
                *reinterpret_cast<uint2*>(orow + 68) = make_uint2(op[0], op[2]);
                *reinterpret_cast<uint2*>(orow + 8 * kActLd + 68) = make_uint2(op[1], op[3]);
                stg128(orow + 96, op[4], op[6], op[8], op[10]);
                stg128(orow + 8 * kActLd + 96, op[5], op[7], op[9], op[11]);
                stg128(orow + 128, op[12], op[14], op[16], op[18]);
                stg128(orow + 8 * kActLd + 128, op[13], op[15], op[17], op[19]);
            }
            arrive_local(c, B_WDONE + 1);
        }
        swiglu_groups<0, 1>(c, accB, hp, hrow0 + 512);
        f_issue<43>(c, accA); swiglu_groups<1, 2>(c, accB, hp, hrow0 + 512);
        f_issue<44>(c, accA); swiglu_groups<2, 3>(c, accB, hp, hrow0 + 512);
        f_issue<45>(c, accA); swiglu_groups<3, 4>(c, accB, hp, hrow0 + 512);
        f_issue<46>(c, accA); swiglu_groups<4, 5>(c, accB, hp, hrow0 + 512);
        f_issue<47>(c, accA); swiglu_groups<5, 6>(c, accB, hp, hrow0 + 512);
        f_issue<48>(c, accA); swiglu_groups<6, 7>(c, accB, hp, hrow0 + 512);
        f_issue<49>(c, accA); swiglu_groups<7, 8>(c, accB, hp, hrow0 + 512);
        arrive_local(c, B_WDONE + 2);
        if (c.w == 0) TRACE(16 + c.par);

        float accG[80];
        g_issue(c, accG, 0, 0, true, 0);
        wg_wait<1>();
        arrive_both(c, B_GEMPTY + 3);
        arrive_both(c, B_GEMPTY + 4);
        swiglu_groups<0, 2>(c, accA, hp, hrow0 + 1024);
        g_issue(c, accG, 1, 0, false, 1); wg_wait<1>(); arrive_both(c, B_GEMPTY + 0);
        swiglu_groups<2, 4>(c, accA, hp, hrow0 + 1024);
        g_issue(c, accG, 2, 0, false, 2); wg_wait<1>(); arrive_both(c, B_GEMPTY + 1);
        swiglu_groups<4, 6>(c, accA, hp, hrow0 + 1024);
        g_issue(c, accG, 3, 0, false, 3); wg_wait<1>(); arrive_both(c, B_GEMPTY + 2);
        swiglu_groups<6, 8>(c, accA, hp, hrow0 + 1024);
        arrive_local(c, B_WDONE + 3);
        g_issue(c, accG, 4, 0, false, 4); wg_wait<1>(); arrive_both(c, B_GEMPTY + 3);
        int gs = 0, gph = 1;
        const int nt = 12 + (half ? 10 - NO0 : NO0);
#pragma unroll 1
        for (int t = 5; t < nt; t++) {
            g_issue(c, accG, gs, gph, false, t);
            wg_wait<1>();
            if (t + 4 < nt) arrive_both(c, B_GEMPTY + (gs == 0 ? 4 : gs - 1));
            if (++gs == 5) { gs = 0; gph ^= 1; }
        }
        if (c.w == 0) TRACE(18 + c.par);
        wg_wait<0>();
        {
            const int R = (lane & 7) + (lane & 8), hi = lane >> 4;
            const uint32_t stg = sb + c.par * 8192 + c.w * 2048;
#pragma unroll
            for (int p = 0; p < 10; p++) {
                const int G = 2 * p;
                const uint32_t addr = (p < 8) ? stg + (p >> 2) * G_STAGE + R * 128 + ((((G & 7) + hi) ^ (R & 7)) << 4)
                                              : stg + 2 * G_STAGE + R * 64 + ((((G & 3) + hi) ^ ((R >> 1) & 3)) << 4);
                stsm4(addr, pack2(accG[4 * G], accG[4 * G + 1]), pack2(accG[4 * G + 2], accG[4 * G + 3]),
                      pack2(accG[4 * G + 4], accG[4 * G + 5]), pack2(accG[4 * G + 6], accG[4 * G + 7]));
            }
            asm volatile("fence.proxy.async.shared::cta;" ::: "memory");
            __syncwarp();
            if (lane == 0) {
                const int row = tile * 64 + c.w * 16;
                tma3_red(&maps.o64, stg, 160 * jj, row, c.par);
                tma3_red(&maps.o64, stg + G_STAGE, 160 * jj + 64, row, c.par);
                tma3_red(&maps.o32, stg + 2 * G_STAGE, 160 * jj + 128, row, c.par);
                asm volatile("cp.async.bulk.commit_group;" ::: "memory");
                asm volatile("cp.async.bulk.wait_group.read 0;" ::: "memory");
            }
        }
        if (c.w == 0) { TRACE(20 + c.par); TRACEG(60 + c.par); }
    }
}

namespace {
typedef CUresult (*EncodeFn)(CUtensorMap*, CUtensorMapDataType, cuuint32_t, void*, const cuuint64_t*, const cuuint64_t*, const cuuint32_t*,
                             const cuuint32_t*, CUtensorMapInterleave, CUtensorMapSwizzle, CUtensorMapL2promotion, CUtensorMapFloatOOBfill);

bool encode(EncodeFn fn, CUtensorMap* m, const void* ptr, int rank, const cuuint64_t* dims, const cuuint64_t* strides, const cuuint32_t* box,
            CUtensorMapSwizzle sw) {
    const cuuint32_t es[5] = {1, 1, 1, 1, 1};
    return fn(m, CU_TENSOR_MAP_DATA_TYPE_BFLOAT16, rank, const_cast<void*>(ptr), dims, strides, box, es, CU_TENSOR_MAP_INTERLEAVE_NONE, sw,
              CU_TENSOR_MAP_L2_PROMOTION_L2_128B, CU_TENSOR_MAP_FLOAT_OOB_FILL_NONE) == CUDA_SUCCESS;
}
}

extern "C" void kernel_launch(void* const* d_in, const int* in_sizes, int n_in, void* d_out, int out_size) {
    (void)in_sizes; (void)n_in; (void)out_size;
    const __nv_bfloat16* x = (const __nv_bfloat16*)d_in[0];
    const __nv_bfloat16* wqkv = (const __nv_bfloat16*)d_in[1];
    const __nv_bfloat16* wo = (const __nv_bfloat16*)d_in[2];
    const __nv_bfloat16* w1 = (const __nv_bfloat16*)d_in[4];
    const __nv_bfloat16* w3 = (const __nv_bfloat16*)d_in[5];
    const __nv_bfloat16* w2 = (const __nv_bfloat16*)d_in[6];

    static EncodeFn fn = nullptr;
    static void* act = nullptr;
    if (!fn) {
        void* p = nullptr;
        cudaDriverEntryPointQueryResult st;
        cudaGetDriverEntryPoint("cuTensorMapEncodeTiled", &p, cudaEnableDefault, &st);
        fn = (EncodeFn)p;
        cudaFuncSetAttribute(fused_block_kernel, cudaFuncAttributeMaxDynamicSharedMemorySize, SM_TOTAL);
        cudaGetSymbolAddress(&act, g_act);
    }
    Maps maps;
    {
        const cuuint64_t d[3] = {640, 1024, 2}, s[2] = {2560, 1280};
        const cuuint32_t b[3] = {64, 64, 2};
        encode(fn, &maps.x, x, 3, d, s, b, CU_TENSOR_MAP_SWIZZLE_128B);
    }
    {
        const cuuint64_t d[3] = {640, 640, 3}, s[2] = {3840, 1280};
        const cuuint32_t b[3] = {64, 16, 3}, br[3] = {16, 16, 3};
        encode(fn, &maps.wq, wqkv, 3, d, s, b, CU_TENSOR_MAP_SWIZZLE_128B);
        encode(fn, &maps.wqr, wqkv, 3, d, s, br, CU_TENSOR_MAP_SWIZZLE_32B);
    }
    {
        const cuuint64_t d[2] = {1536, 640}, s[1] = {3072};
        const cuuint32_t b[2] = {64, 64};
        encode(fn, &maps.w1, w1, 2, d, s, b, CU_TENSOR_MAP_SWIZZLE_128B);
        encode(fn, &maps.w3, w3, 2, d, s, b, CU_TENSOR_MAP_SWIZZLE_128B);
    }
    {
        const cuuint64_t d[2] = {(cuuint64_t)kActLd, (cuuint64_t)kS}, s[1] = {(cuuint64_t)kActLd * 2};
        const cuuint32_t b[2] = {64, 128};
        encode(fn, &maps.act, act, 2, d, s, b, CU_TENSOR_MAP_SWIZZLE_128B);
    }
    {
        const cuuint64_t do5[5] = {640, 2, 80, 4, 2}, d25[5] = {640, 2, 192, 4, 2}, s5[4] = {1280, 10240, 2560, 128};
        const cuuint32_t b5[5] = {64, 2, 4, 4, 2}, b4[4] = {32, 2, 4, 4};
        encode(fn, &maps.wo2, wo, 5, do5, s5, b5, CU_TENSOR_MAP_SWIZZLE_128B);
        encode(fn, &maps.w22, w2, 5, d25, s5, b5, CU_TENSOR_MAP_SWIZZLE_128B);
        encode(fn, &maps.wo1, wo, 4, do5, s5, b4, CU_TENSOR_MAP_SWIZZLE_128B);
        encode(fn, &maps.w21, w2, 4, d25, s5, b4, CU_TENSOR_MAP_SWIZZLE_128B);
    }
    {
        const cuuint64_t d[3] = {640, 1024, 2}, s[2] = {2560, 1280};
        const cuuint32_t b64[3] = {64, 16, 1}, b32[3] = {32, 16, 1};
        encode(fn, &maps.o64, d_out, 3, d, s, b64, CU_TENSOR_MAP_SWIZZLE_128B);
        encode(fn, &maps.o32, d_out, 3, d, s, b32, CU_TENSOR_MAP_SWIZZLE_64B);
    }
    fused_block_kernel<<<128, 384, SM_TOTAL>>>(maps, x, wqkv, w1, w3, wo, w2, (__nv_bfloat16*)d_out);
}
```

```cpp
#include <cuda_runtime.h>
#include <cuda_bf16.h>
#include <cuda.h>
#include <stdint.h>

namespace {

constexpr int kS = 2048, kD = 640, kF = 1536;
constexpr int kActLd = kD + kF;

constexpr uint32_t SM_X = 0;
constexpr uint32_t SM_RING = 163840;
constexpr uint32_t SM_OWN = SM_RING + 3 * 16384;
constexpr uint32_t SM_MISC = 229376;
constexpr uint32_t SM_BAR = SM_MISC;
constexpr uint32_t SM_ST = SM_MISC + 448;
constexpr uint32_t SM_CSB0 = SM_ST + 1024;
constexpr uint32_t SM_CS = SM_CSB0 + 512;
constexpr uint32_t SM_TOTAL = 232448;
constexpr uint32_t G_STAGE = 40960;
static_assert(SM_CS + 1024 <= SM_TOTAL, "smem map");
__host__ __device__ constexpr uint32_t sm_csb(int f) { return f == 0 ? SM_CSB0 : SM_CS + (f - 1) * 512; }

constexpr int B_XFULL = 0;
constexpr int B_RFULL = 10;
constexpr int B_REMPTY = 14;
constexpr int B_GFULL = 18;
constexpr int B_GEMPTY = 23;
constexpr int B_CS = 28;
constexpr int B_ST = 29;
constexpr int B_CSB = 30;
constexpr int B_CSFREE = 33;
constexpr int B_HALOW = 34;
constexpr int B_HALOR = 35;
constexpr int B_WDONE = 37;
constexpr int B_FLAG = 41;
constexpr int B_INIT = 49;
constexpr int B_H1OUT = 50;
constexpr int B_COUNT = 51;
__host__ __device__ constexpr uint32_t bar_count(int i) {
    return ((i >= B_REMPTY && i < B_GFULL) || (i >= B_GEMPTY && i < B_CS)) ? 16
         : (i == B_CSFREE) ? 8
         : (i == B_HALOW) ? 2
         : (i == B_HALOR || i == B_HALOR + 1) ? 5
         : (i == B_WDONE + 1) ? 9
         : (i >= B_WDONE && i < B_FLAG) ? 8 : 1;
}

#define INIT_MODE 1
#define INIT_GAP 300
#define F2_EXPOSED 1
#define SLOT_ROT 0
#define RF_ALIGN 1
#define POLL_GAP 350
#define G_ALIGN 1
#define G_SPLIT 46
#define POLL_FENCE 1
#define G_AUX 1
#define G_AUX_GAP 100
#define WAIT_FAST 1
#define AOFF_KEEP 1
#define STAGGER 0
#define KEEP_ADDR 1
#define X_EARLY 1
#define CS_WAIT 8
#define GATHER_GAP 350
#define JOBA_REV 1
#define TAIL_K 0
#define START_PF 0
#define PAR_INIT 0
#define G_MAP 1
#define G_EARLY 47
#define NH0 4

constexpr int PF_DIST = 6;
#define SILU_TANH 1

__device__ __align__(1024) uint8_t g_act[16 * 34 * 16384];
__device__ __align__(128) unsigned g_csA[4 * 3 * kD];
__device__ __align__(128) unsigned g_csB[2 * 2 * kF];
__device__ __align__(128) unsigned g_stats[kS * 2];
__device__ __align__(128) uint4 g_halo[16 * 8 * 2 * 4 * 5 * 32];
__device__ __align__(128) unsigned g_cntO[16 * 32];
__device__ __align__(128) unsigned g_cntH[16 * 32];
__device__ __align__(128) unsigned g_flagHalo[16 * 8 * 32];
__device__ __align__(128) unsigned g_flagH[2 * 16 * 8 * 32];
#define TP(p) do { } while (0)
#define TRACEFG(slot) do { } while (0)
#define TRACEP(slot) do { } while (0)
#define TRACEF(slot) do { } while (0)
#define TRACE(slot) do { } while (0)
#define TRACEG(slot) do { } while (0)

struct Maps {
    CUtensorMap x, wq, wqr, w1, w3, wo2, wo1, w22, w21, o64, o32, w1c, w3c, wqc;
};

__device__ __forceinline__ long long gtime() { long long t; asm volatile("mov.u64 %0, %%globaltimer;" : "=l"(t)); return t; }
__device__ __forceinline__ uint32_t smem_u32(const void* p) { return (uint32_t)__cvta_generic_to_shared(p); }
__device__ __forceinline__ uint32_t launder(uint32_t x) { uint32_t y; asm volatile("mov.u32 %0, %1;" : "=r"(y) : "r"(x)); return y; }
template <class T> __device__ __forceinline__ T* launder_ptr(T* p) { T* q; asm volatile("mov.u64 %0, %1;" : "=l"(q) : "l"(p)); return q; }
__device__ __forceinline__ void keep_alive(const void* p, int lane) {
    asm volatile("{\n.reg .pred q;\nsetp.eq.s32 q, %1, 77;\n@q st.global.u32 [%0], %1;\n}" ::"l"(p), "r"(lane));
}
__device__ __forceinline__ bool elect_one() {
    uint32_t p;
    asm volatile("{\n.reg .pred P;\nelect.sync _|P, 0xffffffff;\nselp.u32 %0,1,0,P;\n}" : "=r"(p));
    return p;
}
__device__ __forceinline__ void mbar_init(uint32_t bar, uint32_t cnt) { asm volatile("mbarrier.init.shared::cta.b64 [%0], %1;" ::"r"(bar), "r"(cnt)); }
__device__ __forceinline__ void mbar_expect_tx(uint32_t bar, uint32_t bytes) {
    asm volatile("mbarrier.arrive.expect_tx.shared::cta.b64 _, [%0], %1;" ::"r"(bar), "r"(bytes) : "memory");
}
__device__ __forceinline__ void mbar_arrive(uint32_t bar) { asm volatile("mbarrier.arrive.shared::cta.b64 _, [%0];" ::"r"(bar) : "memory"); }
__device__ __forceinline__ void mbar_arrive_cluster(uint32_t bar_cluster_addr) {
    asm volatile("mbarrier.arrive.shared::cluster.b64 _, [%0];" ::"r"(bar_cluster_addr) : "memory");
}
__device__ __forceinline__ uint32_t mapa(uint32_t addr, uint32_t cta) {
    uint32_t r; asm("mapa.shared::cluster.u32 %0, %1, %2;" : "=r"(r) : "r"(addr), "r"(cta)); return r;
}
__device__ __forceinline__ bool mbar_try(uint32_t bar, uint32_t parity) {
    uint32_t ok;
    asm volatile("{\n.reg .pred p;\nmbarrier.try_wait.parity.shared::cta.b64 p, [%1], %2;\nselp.u32 %0,1,0,p;\n}"
                 : "=r"(ok) : "r"(bar), "r"(parity) : "memory");
    return ok;
}
__device__ __forceinline__ void mbar_wait(uint32_t bar, uint32_t parity) {
    if (mbar_try(bar, parity)) return;
    int it = 0;
#pragma unroll 1
    while (!mbar_try(bar, parity)) { if (++it > (1 << 17)) break; }
}
__device__ __forceinline__ void tma2(uint32_t dst, const CUtensorMap* m, int c0, int c1, uint32_t bar) {
    asm volatile("cp.async.bulk.tensor.2d.shared::cluster.global.mbarrier::complete_tx::bytes [%0], [%1, {%3, %4}], [%2];"
                 ::"r"(dst), "l"(m), "r"(bar), "r"(c0), "r"(c1) : "memory");
}
__device__ __forceinline__ void tma3(uint32_t dst, const CUtensorMap* m, int c0, int c1, int c2, uint32_t bar) {
    asm volatile("cp.async.bulk.tensor.3d.shared::cluster.global.mbarrier::complete_tx::bytes [%0], [%1, {%3, %4, %5}], [%2];"
                 ::"r"(dst), "l"(m), "r"(bar), "r"(c0), "r"(c1), "r"(c2) : "memory");
}
__device__ __forceinline__ void tma2_mc(uint32_t dst, const CUtensorMap* m, int c0, int c1, uint32_t bar) {
    asm volatile("cp.async.bulk.tensor.2d.shared::cluster.global.mbarrier::complete_tx::bytes.multicast::cluster [%0], [%1, {%3, %4}], [%2], %5;"
                 ::"r"(dst), "l"(m), "r"(bar), "r"(c0), "r"(c1), "h"((uint16_t)3) : "memory");
}
__device__ __forceinline__ void tma3_mc(uint32_t dst, const CUtensorMap* m, int c0, int c1, int c2, uint32_t bar) {
    asm volatile("cp.async.bulk.tensor.3d.shared::cluster.global.mbarrier::complete_tx::bytes.multicast::cluster [%0], [%1, {%3, %4, %5}], [%2], %6;"
                 ::"r"(dst), "l"(m), "r"(bar), "r"(c0), "r"(c1), "r"(c2), "h"((uint16_t)3) : "memory");
}
__device__ __forceinline__ void tma4_mc(uint32_t dst, const CUtensorMap* m, int c0, int c2, uint32_t bar) {
    asm volatile("cp.async.bulk.tensor.4d.shared::cluster.global.mbarrier::complete_tx::bytes.multicast::cluster [%0], [%1, {%3, %5, %4, %5}], [%2], %6;"
                 ::"r"(dst), "l"(m), "r"(bar), "r"(c0), "r"(c2), "r"(0), "h"((uint16_t)3) : "memory");
}
__device__ __forceinline__ void tma5_mc(uint32_t dst, const CUtensorMap* m, int c0, int c2, uint32_t bar) {
    asm volatile("cp.async.bulk.tensor.5d.shared::cluster.global.mbarrier::complete_tx::bytes.multicast::cluster [%0], [%1, {%3, %5, %4, %5, %5}], [%2], %6;"
                 ::"r"(dst), "l"(m), "r"(bar), "r"(c0), "r"(c2), "r"(0), "h"((uint16_t)3) : "memory");
}
__device__ __forceinline__ void bulk_g2s(uint32_t dst, const void* src, uint32_t bytes, uint32_t bar) {
    asm volatile("cp.async.bulk.shared::cluster.global.mbarrier::complete_tx::bytes [%0], [%1], %2, [%3];"
                 ::"r"(dst), "l"(src), "r"(bytes), "r"(bar) : "memory");
}
__device__ __forceinline__ uint4 lds128(uint32_t a) {
    uint4 v; asm volatile("ld.shared.v4.u32 {%0,%1,%2,%3}, [%4];" : "=r"(v.x), "=r"(v.y), "=r"(v.z), "=r"(v.w) : "r"(a) : "memory"); return v;
}
__device__ __forceinline__ void sts128(uint32_t a, uint4 v) {
    asm volatile("st.shared.v4.u32 [%0], {%1,%2,%3,%4};" ::"r"(a), "r"(v.x), "r"(v.y), "r"(v.z), "r"(v.w) : "memory");
}
__device__ __forceinline__ void prefetch_map(const CUtensorMap* m) { asm volatile("prefetch.tensormap [%0];" ::"l"(m) : "memory"); }
__device__ __forceinline__ void prefetch_l2(const void* p, uint32_t bytes) {
    asm volatile("cp.async.bulk.prefetch.L2.global [%0], %1;" ::"l"(p), "r"(bytes) : "memory");
}
__device__ __forceinline__ void wg_fence() { asm volatile("wgmma.fence.sync.aligned;" ::: "memory"); }
__device__ __forceinline__ void wg_commit() { asm volatile("wgmma.commit_group.sync.aligned;" ::: "memory"); }
template <int N> __device__ __forceinline__ void wg_wait() { asm volatile("wgmma.wait_group.sync.aligned %0;" ::"n"(N) : "memory"); }
__device__ __forceinline__ unsigned ld_acquire(const unsigned* p) {
    unsigned v; asm volatile("ld.acquire.gpu.global.u32 %0, [%1];" : "=r"(v) : "l"(p) : "memory"); return v;
}
__device__ __forceinline__ void fence_gpu() { asm volatile("fence.acq_rel.gpu;" ::: "memory"); }
__device__ __forceinline__ void fence_async_global() { asm volatile("fence.proxy.async.global;" ::: "memory"); }
__device__ __forceinline__ void red_add(unsigned* p, unsigned v) { asm volatile("red.relaxed.gpu.global.add.u32 [%0], %1;" ::"l"(p), "r"(v) : "memory"); }
__device__ __forceinline__ void st_relaxed(unsigned* p, unsigned v) { asm volatile("st.relaxed.gpu.global.u32 [%0], %1;" ::"l"(p), "r"(v) : "memory"); }
__device__ __forceinline__ unsigned ld_relaxed(const unsigned* p) {
    unsigned v; asm volatile("ld.relaxed.gpu.global.u32 %0, [%1];" : "=r"(v) : "l"(p) : "memory"); return v;
}
__device__ __forceinline__ unsigned tagged(unsigned tag, float v) { return ((__float_as_uint(v) + 8u) & ~15u) | (tag & 15u); }
__device__ __forceinline__ bool tag_ok(const uint4& v, unsigned tag) { return (((v.x ^ tag) | (v.y ^ tag) | (v.z ^ tag) | (v.w ^ tag)) & 15u) == 0; }
__device__ __forceinline__ float tag_val(unsigned v) { return __uint_as_float(v & ~15u); }
__device__ __forceinline__ void st_tag(unsigned* p, unsigned a) { asm volatile("st.relaxed.gpu.global.u32 [%0], %1;" ::"l"(p), "r"(a) : "memory"); }
__device__ __forceinline__ void st_tag2(unsigned* p, unsigned a, unsigned b) {
    asm volatile("st.relaxed.gpu.global.v2.u32 [%0], {%1, %2};" ::"l"(p), "r"(a), "r"(b) : "memory");
}
__device__ __forceinline__ void st_tag4(unsigned* p, unsigned a, unsigned b, unsigned c, unsigned d) {
    asm volatile("st.relaxed.gpu.global.v4.u32 [%0], {%1, %2, %3, %4};" ::"l"(p), "r"(a), "r"(b), "r"(c), "r"(d) : "memory");
}
__device__ __forceinline__ uint4 ld_tag4(const unsigned* p) {
    uint4 v; asm volatile("ld.relaxed.gpu.global.v4.u32 {%0,%1,%2,%3}, [%4];" : "=r"(v.x), "=r"(v.y), "=r"(v.z), "=r"(v.w) : "l"(p) : "memory"); return v;
}
__device__ __forceinline__ void poll_ge(const unsigned* p, unsigned target) {
    int it = 0;
#pragma unroll 1
    while ((int)(ld_acquire(p) - target) < 0) { if (++it > (1 << 16)) break; }
}
__device__ __forceinline__ void spin(int cycles) { const long long t0 = clock64(); while (clock64() - t0 < cycles) { } }
#define PROXY_FENCE() fence_async_global()
__device__ __forceinline__ void gather2(const unsigned* p0, const unsigned* p1, unsigned tag, uint4& r0, uint4& r1) {
    uint4 a0 = ld_tag4(p0), a1 = ld_tag4(p1);
    spin(GATHER_GAP);
    uint4 b0 = ld_tag4(p0), b1 = ld_tag4(p1);
    spin(GATHER_GAP);
    uint4 c0 = ld_tag4(p0), c1 = ld_tag4(p1);
#pragma unroll 1
    for (int it = 0; it < (1 << 14); it++) {
        if (__all_sync(0xffffffffu, tag_ok(a0, tag) && tag_ok(a1, tag))) { r0 = a0; r1 = a1; return; }
        a0 = ld_tag4(p0); a1 = ld_tag4(p1);
        if (__all_sync(0xffffffffu, tag_ok(b0, tag) && tag_ok(b1, tag))) { r0 = b0; r1 = b1; return; }
        b0 = ld_tag4(p0); b1 = ld_tag4(p1);
        if (__all_sync(0xffffffffu, tag_ok(c0, tag) && tag_ok(c1, tag))) { r0 = c0; r1 = c1; return; }
        c0 = ld_tag4(p0); c1 = ld_tag4(p1);
    }
    r0 = a0; r1 = a1;
}
__device__ __forceinline__ void poll_multi(const unsigned* p, unsigned target, uint32_t bar, bool active) {
    bool done = !active;
    unsigned v0 = 0, v1 = 0, v2 = 0;
    if (!done) v0 = ld_relaxed(p);
    spin(POLL_GAP);
    if (!done) v1 = ld_relaxed(p);
    spin(POLL_GAP);
    if (!done) v2 = ld_relaxed(p);
#pragma unroll 1
    for (int it = 0; it < (1 << 15); it++) {
        if (!done && (int)(v0 - target) >= 0) { PROXY_FENCE(); mbar_arrive(bar); done = true; }
        if (__all_sync(0xffffffffu, done)) return;
        if (!done) v0 = ld_relaxed(p);
        if (!done && (int)(v1 - target) >= 0) { PROXY_FENCE(); mbar_arrive(bar); done = true; }
        if (__all_sync(0xffffffffu, done)) return;
        if (!done) v1 = ld_relaxed(p);
        if (!done && (int)(v2 - target) >= 0) { PROXY_FENCE(); mbar_arrive(bar); done = true; }
        if (__all_sync(0xffffffffu, done)) return;
        if (!done) v2 = ld_relaxed(p);
    }
    if (!done) mbar_arrive(bar);
}
template <int ID, int N> __device__ __forceinline__ void bar_sync() { asm volatile("bar.sync %0, %1;" ::"n"(ID), "n"(N) : "memory"); }
__device__ __forceinline__ float ex2(float x) { float y; asm("ex2.approx.ftz.f32 %0, %1;" : "=f"(y) : "f"(x)); return y; }
__device__ __forceinline__ float rcp(float x) { float y; asm("rcp.approx.ftz.f32 %0, %1;" : "=f"(y) : "f"(x)); return y; }
__device__ __forceinline__ float tanh_fast(float x) { float y; asm("tanh.approx.f32 %0, %1;" : "=f"(y) : "f"(x)); return y; }
__device__ __forceinline__ uint32_t badd2(uint32_t a, uint32_t b) { uint32_t d; asm("add.rn.bf16x2 %0, %1, %2;" : "=r"(d) : "r"(a), "r"(b)); return d; }
__device__ __forceinline__ uint32_t lds32(uint32_t a) { uint32_t v; asm volatile("ld.shared.u32 %0, [%1];" : "=r"(v) : "r"(a) : "memory"); return v; }
__device__ __forceinline__ uint32_t pack2(float lo, float hi) {
    uint32_t r; asm("cvt.rn.bf16x2.f32 %0, %1, %2;" : "=r"(r) : "f"(hi), "f"(lo)); return r;
}
__device__ __forceinline__ float bf_lo(uint32_t v) { return __uint_as_float(v << 16); }
__device__ __forceinline__ float bf_hi(uint32_t v) { return __uint_as_float(v & 0xffff0000u); }
__device__ __forceinline__ float2 lds64_const(uint32_t a) { float2 v; asm("ld.shared.v2.f32 {%0,%1}, [%2];" : "=f"(v.x), "=f"(v.y) : "r"(a)); return v; }
__device__ __forceinline__ float2 lds64(uint32_t a) { float2 v; asm volatile("ld.shared.v2.f32 {%0,%1}, [%2];" : "=f"(v.x), "=f"(v.y) : "r"(a)); return v; }
__device__ __forceinline__ void mma16(float (&c)[4], uint32_t a0, uint32_t a1, uint32_t a2, uint32_t a3, uint32_t b0, uint32_t b1) {
    asm("mma.sync.aligned.m16n8k16.row.col.f32.bf16.bf16.f32 {%0,%1,%2,%3}, {%4,%5,%6,%7}, {%8,%9}, {%0,%1,%2,%3};"
        : "+f"(c[0]), "+f"(c[1]), "+f"(c[2]), "+f"(c[3]) : "r"(a0), "r"(a1), "r"(a2), "r"(a3), "r"(b0), "r"(b1));
}
__device__ __forceinline__ void mma8(float (&c)[4], uint32_t a0, uint32_t a1, uint32_t b0) {
    asm("mma.sync.aligned.m16n8k8.row.col.f32.bf16.bf16.f32 {%0,%1,%2,%3}, {%4,%5}, {%6}, {%0,%1,%2,%3};"
        : "+f"(c[0]), "+f"(c[1]), "+f"(c[2]), "+f"(c[3]) : "r"(a0), "r"(a1), "r"(b0));
}
__device__ __forceinline__ void mma16v(float (&d)[4], uint32_t a0, uint32_t a1, uint32_t a2, uint32_t a3, uint32_t b0, uint32_t b1,
                                       float c0, float c1, float c2, float c3) {
    asm volatile("mma.sync.aligned.m16n8k16.row.col.f32.bf16.bf16.f32 {%0,%1,%2,%3}, {%4,%5,%6,%7}, {%8,%9}, {%10,%11,%12,%13};"
        : "=f"(d[0]), "=f"(d[1]), "=f"(d[2]), "=f"(d[3]) : "r"(a0), "r"(a1), "r"(a2), "r"(a3), "r"(b0), "r"(b1), "f"(c0), "f"(c1), "f"(c2), "f"(c3));
}
__device__ __forceinline__ void mma8v(float (&c)[4], uint32_t a0, uint32_t a1, uint32_t b0) {
    asm volatile("mma.sync.aligned.m16n8k8.row.col.f32.bf16.bf16.f32 {%0,%1,%2,%3}, {%4,%5}, {%6}, {%0,%1,%2,%3};"
        : "+f"(c[0]), "+f"(c[1]), "+f"(c[2]), "+f"(c[3]) : "r"(a0), "r"(a1), "r"(b0));
}
__device__ __forceinline__ uint32_t pack2v(float lo, float hi) {
    uint32_t r; asm volatile("cvt.rn.bf16x2.f32 %0, %1, %2;" : "=r"(r) : "f"(hi), "f"(lo)); return r;
}
__device__ __forceinline__ uint32_t andv(uint32_t a, uint32_t b) {
    uint32_t r; asm volatile("and.b32 %0, %1, %2;" : "=r"(r) : "r"(a), "r"(b)); return r;
}
__device__ __forceinline__ uint32_t movv(uint32_t a) {
    uint32_t r; asm volatile("mov.b32 %0, %1;" : "=r"(r) : "r"(a)); return r;
}
__device__ __forceinline__ uint32_t movm(uint32_t a) {
    uint32_t d; asm volatile("movmatrix.sync.aligned.m8n8.trans.b16 %0, %1;" : "=r"(d) : "r"(a)); return d;
}

__device__ __forceinline__ void wgmma_n48(float (&d)[24], uint32_t alo, uint32_t ahi, uint32_t blo, uint32_t bhi, int sd) {
    asm volatile("{\n.reg .pred p;\n.reg .b64 da, db;\nsetp.ne.b32 p, %28, 0;\nmov.b64 da, {%24,%25};\nmov.b64 db, {%26,%27};\n"
        "wgmma.mma_async.sync.aligned.m64n48k16.f32.bf16.bf16 {"
        "%0,%1,%2,%3,%4,%5,%6,%7,%8,%9,%10,%11,%12,%13,%14,%15,"
        "%16,%17,%18,%19,%20,%21,%22,%23"
        "}, da, db, p, 1, 1, 0, 1;\n}\n"
        : "+f"(d[0]), "+f"(d[1]), "+f"(d[2]), "+f"(d[3]), "+f"(d[4]), "+f"(d[5]), "+f"(d[6]), "+f"(d[7]),
          "+f"(d[8]), "+f"(d[9]), "+f"(d[10]), "+f"(d[11]), "+f"(d[12]), "+f"(d[13]), "+f"(d[14]), "+f"(d[15]),
          "+f"(d[16]), "+f"(d[17]), "+f"(d[18]), "+f"(d[19]), "+f"(d[20]), "+f"(d[21]), "+f"(d[22]), "+f"(d[23])
        : "r"(alo), "r"(ahi), "r"(blo), "r"(bhi), "r"(sd));
}
__device__ __forceinline__ void wgmma_n128(float (&d)[64], uint32_t alo, uint32_t ahi, uint32_t blo, uint32_t bhi, int sd) {
    asm volatile("{\n.reg .pred p;\n.reg .b64 da, db;\nsetp.ne.b32 p, %68, 0;\nmov.b64 da, {%64,%65};\nmov.b64 db, {%66,%67};\n"
        "wgmma.mma_async.sync.aligned.m64n128k16.f32.bf16.bf16 {"
        "%0,%1,%2,%3,%4,%5,%6,%7,%8,%9,%10,%11,%12,%13,%14,%15,"
        "%16,%17,%18,%19,%20,%21,%22,%23,%24,%25,%26,%27,%28,%29,%30,%31,"
        "%32,%33,%34,%35,%36,%37,%38,%39,%40,%41,%42,%43,%44,%45,%46,%47,"
        "%48,%49,%50,%51,%52,%53,%54,%55,%56,%57,%58,%59,%60,%61,%62,%63"
        "}, da, db, p, 1, 1, 0, 1;\n}\n"
        : "+f"(d[0]), "+f"(d[1]), "+f"(d[2]), "+f"(d[3]), "+f"(d[4]), "+f"(d[5]), "+f"(d[6]), "+f"(d[7]),
          "+f"(d[8]), "+f"(d[9]), "+f"(d[10]), "+f"(d[11]), "+f"(d[12]), "+f"(d[13]), "+f"(d[14]), "+f"(d[15]),
          "+f"(d[16]), "+f"(d[17]), "+f"(d[18]), "+f"(d[19]), "+f"(d[20]), "+f"(d[21]), "+f"(d[22]), "+f"(d[23]),
          "+f"(d[24]), "+f"(d[25]), "+f"(d[26]), "+f"(d[27]), "+f"(d[28]), "+f"(d[29]), "+f"(d[30]), "+f"(d[31]),
          "+f"(d[32]), "+f"(d[33]), "+f"(d[34]), "+f"(d[35]), "+f"(d[36]), "+f"(d[37]), "+f"(d[38]), "+f"(d[39]),
          "+f"(d[40]), "+f"(d[41]), "+f"(d[42]), "+f"(d[43]), "+f"(d[44]), "+f"(d[45]), "+f"(d[46]), "+f"(d[47]),
          "+f"(d[48]), "+f"(d[49]), "+f"(d[50]), "+f"(d[51]), "+f"(d[52]), "+f"(d[53]), "+f"(d[54]), "+f"(d[55]),
          "+f"(d[56]), "+f"(d[57]), "+f"(d[58]), "+f"(d[59]), "+f"(d[60]), "+f"(d[61]), "+f"(d[62]), "+f"(d[63])
        : "r"(alo), "r"(ahi), "r"(blo), "r"(bhi), "r"(sd));
}
__device__ __forceinline__ void wgmma_n160(float (&d)[80], uint32_t alo, uint32_t ahi, uint32_t blo, uint32_t bhi, int sd) {
    asm volatile("{\n.reg .pred p;\n.reg .b64 da, db;\nsetp.ne.b32 p, %84, 0;\nmov.b64 da, {%80,%81};\nmov.b64 db, {%82,%83};\n"
        "wgmma.mma_async.sync.aligned.m64n160k16.f32.bf16.bf16 {"
        "%0,%1,%2,%3,%4,%5,%6,%7,%8,%9,%10,%11,%12,%13,%14,%15,"
        "%16,%17,%18,%19,%20,%21,%22,%23,%24,%25,%26,%27,%28,%29,%30,%31,"
        "%32,%33,%34,%35,%36,%37,%38,%39,%40,%41,%42,%43,%44,%45,%46,%47,"
        "%48,%49,%50,%51,%52,%53,%54,%55,%56,%57,%58,%59,%60,%61,%62,%63,"
        "%64,%65,%66,%67,%68,%69,%70,%71,%72,%73,%74,%75,%76,%77,%78,%79"
        "}, da, db, p, 1, 1, 0, 1;\n}\n"
        : "+f"(d[0]), "+f"(d[1]), "+f"(d[2]), "+f"(d[3]), "+f"(d[4]), "+f"(d[5]), "+f"(d[6]), "+f"(d[7]),
          "+f"(d[8]), "+f"(d[9]), "+f"(d[10]), "+f"(d[11]), "+f"(d[12]), "+f"(d[13]), "+f"(d[14]), "+f"(d[15]),
          "+f"(d[16]), "+f"(d[17]), "+f"(d[18]), "+f"(d[19]), "+f"(d[20]), "+f"(d[21]), "+f"(d[22]), "+f"(d[23]),
          "+f"(d[24]), "+f"(d[25]), "+f"(d[26]), "+f"(d[27]), "+f"(d[28]), "+f"(d[29]), "+f"(d[30]), "+f"(d[31]),
          "+f"(d[32]), "+f"(d[33]), "+f"(d[34]), "+f"(d[35]), "+f"(d[36]), "+f"(d[37]), "+f"(d[38]), "+f"(d[39]),
          "+f"(d[40]), "+f"(d[41]), "+f"(d[42]), "+f"(d[43]), "+f"(d[44]), "+f"(d[45]), "+f"(d[46]), "+f"(d[47]),
          "+f"(d[48]), "+f"(d[49]), "+f"(d[50]), "+f"(d[51]), "+f"(d[52]), "+f"(d[53]), "+f"(d[54]), "+f"(d[55]),
          "+f"(d[56]), "+f"(d[57]), "+f"(d[58]), "+f"(d[59]), "+f"(d[60]), "+f"(d[61]), "+f"(d[62]), "+f"(d[63]),
          "+f"(d[64]), "+f"(d[65]), "+f"(d[66]), "+f"(d[67]), "+f"(d[68]), "+f"(d[69]), "+f"(d[70]), "+f"(d[71]),
          "+f"(d[72]), "+f"(d[73]), "+f"(d[74]), "+f"(d[75]), "+f"(d[76]), "+f"(d[77]), "+f"(d[78]), "+f"(d[79])
        : "r"(alo), "r"(ahi), "r"(blo), "r"(bhi), "r"(sd));
}
__device__ __forceinline__ void wgmma_n192(float (&d)[96], uint32_t alo, uint32_t ahi, uint32_t blo, uint32_t bhi, int sd) {
    asm volatile("{\n.reg .pred p;\n.reg .b64 da, db;\nsetp.ne.b32 p, %100, 0;\nmov.b64 da, {%96,%97};\nmov.b64 db, {%98,%99};\n"
        "wgmma.mma_async.sync.aligned.m64n192k16.f32.bf16.bf16 {"
        "%0,%1,%2,%3,%4,%5,%6,%7,%8,%9,%10,%11,%12,%13,%14,%15,"
        "%16,%17,%18,%19,%20,%21,%22,%23,%24,%25,%26,%27,%28,%29,%30,%31,"
        "%32,%33,%34,%35,%36,%37,%38,%39,%40,%41,%42,%43,%44,%45,%46,%47,"
        "%48,%49,%50,%51,%52,%53,%54,%55,%56,%57,%58,%59,%60,%61,%62,%63,"
        "%64,%65,%66,%67,%68,%69,%70,%71,%72,%73,%74,%75,%76,%77,%78,%79,"
        "%80,%81,%82,%83,%84,%85,%86,%87,%88,%89,%90,%91,%92,%93,%94,%95"
        "}, da, db, p, 1, 1, 0, 1;\n}\n"
        : "+f"(d[0]), "+f"(d[1]), "+f"(d[2]), "+f"(d[3]), "+f"(d[4]), "+f"(d[5]), "+f"(d[6]), "+f"(d[7]),
          "+f"(d[8]), "+f"(d[9]), "+f"(d[10]), "+f"(d[11]), "+f"(d[12]), "+f"(d[13]), "+f"(d[14]), "+f"(d[15]),
          "+f"(d[16]), "+f"(d[17]), "+f"(d[18]), "+f"(d[19]), "+f"(d[20]), "+f"(d[21]), "+f"(d[22]), "+f"(d[23]),
          "+f"(d[24]), "+f"(d[25]), "+f"(d[26]), "+f"(d[27]), "+f"(d[28]), "+f"(d[29]), "+f"(d[30]), "+f"(d[31]),
          "+f"(d[32]), "+f"(d[33]), "+f"(d[34]), "+f"(d[35]), "+f"(d[36]), "+f"(d[37]), "+f"(d[38]), "+f"(d[39]),
          "+f"(d[40]), "+f"(d[41]), "+f"(d[42]), "+f"(d[43]), "+f"(d[44]), "+f"(d[45]), "+f"(d[46]), "+f"(d[47]),
          "+f"(d[48]), "+f"(d[49]), "+f"(d[50]), "+f"(d[51]), "+f"(d[52]), "+f"(d[53]), "+f"(d[54]), "+f"(d[55]),
          "+f"(d[56]), "+f"(d[57]), "+f"(d[58]), "+f"(d[59]), "+f"(d[60]), "+f"(d[61]), "+f"(d[62]), "+f"(d[63]),
          "+f"(d[64]), "+f"(d[65]), "+f"(d[66]), "+f"(d[67]), "+f"(d[68]), "+f"(d[69]), "+f"(d[70]), "+f"(d[71]),
          "+f"(d[72]), "+f"(d[73]), "+f"(d[74]), "+f"(d[75]), "+f"(d[76]), "+f"(d[77]), "+f"(d[78]), "+f"(d[79]),
          "+f"(d[80]), "+f"(d[81]), "+f"(d[82]), "+f"(d[83]), "+f"(d[84]), "+f"(d[85]), "+f"(d[86]), "+f"(d[87]),
          "+f"(d[88]), "+f"(d[89]), "+f"(d[90]), "+f"(d[91]), "+f"(d[92]), "+f"(d[93]), "+f"(d[94]), "+f"(d[95])
        : "r"(alo), "r"(ahi), "r"(blo), "r"(bhi), "r"(sd));
}
__device__ __forceinline__ void wgmma_n96(float (&d)[48], uint32_t alo, uint32_t ahi, uint32_t blo, uint32_t bhi, int sd) {
    asm volatile("{\n.reg .pred p;\n.reg .b64 da, db;\nsetp.ne.b32 p, %52, 0;\nmov.b64 da, {%48,%49};\nmov.b64 db, {%50,%51};\n"
        "wgmma.mma_async.sync.aligned.m64n96k16.f32.bf16.bf16 {"
        "%0,%1,%2,%3,%4,%5,%6,%7,%8,%9,%10,%11,%12,%13,%14,%15,"
        "%16,%17,%18,%19,%20,%21,%22,%23,%24,%25,%26,%27,%28,%29,%30,%31,"
        "%32,%33,%34,%35,%36,%37,%38,%39,%40,%41,%42,%43,%44,%45,%46,%47"
        "}, da, db, p, 1, 1, 0, 1;\n}\n"
        : "+f"(d[0]), "+f"(d[1]), "+f"(d[2]), "+f"(d[3]), "+f"(d[4]), "+f"(d[5]), "+f"(d[6]), "+f"(d[7]),
          "+f"(d[8]), "+f"(d[9]), "+f"(d[10]), "+f"(d[11]), "+f"(d[12]), "+f"(d[13]), "+f"(d[14]), "+f"(d[15]),
          "+f"(d[16]), "+f"(d[17]), "+f"(d[18]), "+f"(d[19]), "+f"(d[20]), "+f"(d[21]), "+f"(d[22]), "+f"(d[23]),
          "+f"(d[24]), "+f"(d[25]), "+f"(d[26]), "+f"(d[27]), "+f"(d[28]), "+f"(d[29]), "+f"(d[30]), "+f"(d[31]),
          "+f"(d[32]), "+f"(d[33]), "+f"(d[34]), "+f"(d[35]), "+f"(d[36]), "+f"(d[37]), "+f"(d[38]), "+f"(d[39]),
          "+f"(d[40]), "+f"(d[41]), "+f"(d[42]), "+f"(d[43]), "+f"(d[44]), "+f"(d[45]), "+f"(d[46]), "+f"(d[47])
        : "r"(alo), "r"(ahi), "r"(blo), "r"(bhi), "r"(sd));
}
__device__ __forceinline__ void wgmma_n64(float (&d)[32], uint32_t alo, uint32_t ahi, uint32_t blo, uint32_t bhi, int sd) {
    asm volatile("{\n.reg .pred p;\n.reg .b64 da, db;\nsetp.ne.b32 p, %36, 0;\nmov.b64 da, {%32,%33};\nmov.b64 db, {%34,%35};\n"
        "wgmma.mma_async.sync.aligned.m64n64k16.f32.bf16.bf16 {"
        "%0,%1,%2,%3,%4,%5,%6,%7,%8,%9,%10,%11,%12,%13,%14,%15,"
        "%16,%17,%18,%19,%20,%21,%22,%23,%24,%25,%26,%27,%28,%29,%30,%31"
        "}, da, db, p, 1, 1, 0, 1;\n}\n"
        : "+f"(d[0]), "+f"(d[1]), "+f"(d[2]), "+f"(d[3]), "+f"(d[4]), "+f"(d[5]), "+f"(d[6]), "+f"(d[7]),
          "+f"(d[8]), "+f"(d[9]), "+f"(d[10]), "+f"(d[11]), "+f"(d[12]), "+f"(d[13]), "+f"(d[14]), "+f"(d[15]),
          "+f"(d[16]), "+f"(d[17]), "+f"(d[18]), "+f"(d[19]), "+f"(d[20]), "+f"(d[21]), "+f"(d[22]), "+f"(d[23]),
          "+f"(d[24]), "+f"(d[25]), "+f"(d[26]), "+f"(d[27]), "+f"(d[28]), "+f"(d[29]), "+f"(d[30]), "+f"(d[31])
        : "r"(alo), "r"(ahi), "r"(blo), "r"(bhi), "r"(sd));
}

constexpr uint32_t HI_128 = 0x40000040u;
constexpr uint32_t HI_64 = 0x80000020u;
constexpr uint32_t HI_32 = 0xC0000010u;
__device__ __forceinline__ constexpr uint32_t lbo(uint32_t bytes) { return (bytes >> 4) << 16; }

struct Ctx {
    uint32_t sb;
    uint32_t bar;
    uint32_t rbar;
    uint32_t a_lo;
    uint32_t b_lo;
    int lane, q, g, w, par;
    uint32_t aoff;
    float m0, m1, r0, r1;
    float ga0, ga1, gb0, gb1;
};

__device__ __forceinline__ void arrive_both(const Ctx& c, int bar_idx) {
    if (c.lane < 2) mbar_arrive_cluster(c.rbar + bar_idx * 8);
}
__device__ __forceinline__ void arrive_local(const Ctx& c, int bar_idx) {
    __syncwarp();
    if (c.lane == 0) mbar_arrive(c.bar + bar_idx * 8);
}

__device__ __forceinline__ void stsm4(uint32_t addr, uint32_t a, uint32_t b, uint32_t c, uint32_t d) {
    asm volatile("stmatrix.sync.aligned.m8n8.x4.shared.b16 [%0], {%1, %2, %3, %4};" ::"r"(addr), "r"(a), "r"(b), "r"(c), "r"(d) : "memory");
}
__device__ __forceinline__ void tma3_store(const CUtensorMap* m, uint32_t src, int c0, int c1, int c2) {
    asm volatile("cp.async.bulk.tensor.3d.global.shared::cta.tile.bulk_group [%0, {%2, %3, %4}], [%1];"
                 ::"l"(m), "r"(src), "r"(c0), "r"(c1), "r"(c2) : "memory");
}
__device__ __forceinline__ void tma3_red(const CUtensorMap* m, uint32_t src, int c0, int c1, int c2) {
    asm volatile("cp.reduce.async.bulk.tensor.3d.global.shared::cta.add.tile.bulk_group [%0, {%2, %3, %4}], [%1];"
                 ::"l"(m), "r"(src), "r"(c0), "r"(c1), "r"(c2) : "memory");
}

template <bool SCALE>
__device__ __forceinline__ void ln_pack(const Ctx& c, const float* a, const float2 cs, uint32_t& lo, uint32_t& hi) {
    if (SCALE) {
        lo = pack2(fmaf(c.m0, cs.x, a[0]) * c.r0, fmaf(c.m0, cs.y, a[1]) * c.r0);
        hi = pack2(fmaf(c.m1, cs.x, a[2]) * c.r1, fmaf(c.m1, cs.y, a[3]) * c.r1);
    } else {
        lo = pack2(fmaf(c.m0, cs.x, a[0]), fmaf(c.m0, cs.y, a[1]));
        hi = pack2(fmaf(c.m1, cs.x, a[2]), fmaf(c.m1, cs.y, a[3]));
    }
}
__host__ __device__ constexpr int qg_part(int i) { return i < 10 ? 1 : i < 20 ? 2 : 0; }
template <bool RF> __host__ __device__ constexpr int qg_main(int G) { return RF ? (G < 2 ? -1 - G : G - 2) : (G < 8 ? G : -1 - (G - 8)); }
template <bool RF> __host__ __device__ constexpr int qg_col(int i) {
    return qg_main<RF>(i % 10) >= 0 ? qg_part(i) * 64 + qg_main<RF>(i % 10) * 8 : 192 + qg_part(i) * 16 + (-1 - qg_main<RF>(i % 10)) * 8;
}
template <bool RF, int I0, int I1>
__device__ __forceinline__ void qkv_pre(const Ctx& c, float2 (&cs)[8]) {
#pragma unroll
    for (int i = I0; i < I1; i++) cs[i - I0] = lds64(c.sb + SM_CS + (qg_col<RF>(i) + 2 * c.q) * 4);
}
template <bool RF, int I0, int I1>
__device__ __forceinline__ void qkv_pack(const Ctx& c, const float2 (&cs)[8], const float (&a1)[96], const float (&a2)[24],
                                         uint32_t (&qp)[20], uint32_t (&kp)[20], uint32_t (&vp)[20]) {
#pragma unroll
    for (int i = I0; i < I1; i++) {
        const int P = qg_part(i), G = i % 10, M = qg_main<RF>(G);
        const float* a = (M >= 0) ? &a1[P * 32 + M * 4] : &a2[P * 8 + (-1 - M) * 4];
        if (P == 0) ln_pack<false>(c, a, cs[i - I0], qp[2 * G], qp[2 * G + 1]);
        else if (P == 1) ln_pack<true>(c, a, cs[i - I0], kp[2 * G], kp[2 * G + 1]);
        else ln_pack<true>(c, a, cs[i - I0], vp[2 * G], vp[2 * G + 1]);
    }
}

__device__ __forceinline__ void attn_prep(const Ctx& c, bool first, const uint32_t (&qp)[20], uint32_t (&qs)[4][2], float& nq) {
    const uint32_t lo = (c.q < 2) ? 0xffffffffu : 0u, hi = ~lo;
#pragma unroll
    for (int h = 0; h < 4; h++) {
        const int GS = (h < 2) ? 2 : 7;
        qs[h][0] = andv(qp[2 * GS], (h & 1) ? hi : lo);
        qs[h][1] = andv(qp[2 * GS + 1], (h & 1) ? hi : lo);
    }
    nq = __uint_as_float(movv(first ? 0xff800000u : 0u));
}
template <int H>
__device__ __forceinline__ void attn_logits(const uint32_t (&qp)[20], const uint32_t (&qs)[4][2], const uint32_t (&kp)[20],
                                            const uint32_t (&hk)[10], float nq, float (&sP)[4], float (&sL)[4], float (&sU)[4]) {
    constexpr int GA = (H == 0) ? 0 : (H == 1) ? 3 : (H == 2) ? 5 : 8;
    constexpr int GS = (H < 2) ? 2 : 7;
    mma16v(sP, qp[2 * GA], qp[2 * GA + 1], qp[2 * GA + 2], qp[2 * GA + 3], hk[GA], hk[GA + 1], nq, nq, nq, nq);
    mma16v(sL, qp[2 * GA], qp[2 * GA + 1], qp[2 * GA + 2], qp[2 * GA + 3], kp[2 * GA], kp[2 * GA + 2], 0.f, 0.f, 0.f, 0.f);
    mma16v(sU, qp[2 * GA], qp[2 * GA + 1], qp[2 * GA + 2], qp[2 * GA + 3], kp[2 * GA + 1], kp[2 * GA + 3], 0.f, 0.f, 0.f, 0.f);
    mma8v(sP, qs[H][0], qs[H][1], hk[GS]);
    mma8v(sL, qs[H][0], qs[H][1], kp[2 * GS]);
    mma8v(sU, qs[H][0], qs[H][1], kp[2 * GS + 1]);
}
__device__ __forceinline__ void attn_select(const Ctx& c, const float (&lg)[4][3][4], float (&s)[4][4]) {
    const bool gt0 = 2 * c.q > c.g, gt1 = 2 * c.q + 1 > c.g;
#pragma unroll
    for (int h = 0; h < 4; h++) {
        s[h][0] = gt0 ? lg[h][0][0] : lg[h][1][0];
        s[h][1] = gt1 ? lg[h][0][1] : lg[h][1][1];
        s[h][2] = gt0 ? lg[h][1][2] : lg[h][2][2];
        s[h][3] = gt1 ? lg[h][1][3] : lg[h][2][3];
    }
}
constexpr float kScale = 0.22360679774997896f * 1.4426950408889634f;
__device__ __forceinline__ void attn_max(const float (&s)[4][4], float (&m)[4][2]) {
#pragma unroll
    for (int h = 0; h < 4; h++) { m[h][0] = fmaxf(s[h][0], s[h][1]); m[h][1] = fmaxf(s[h][2], s[h][3]); }
#pragma unroll
    for (int o = 1; o < 4; o <<= 1) {
#pragma unroll
        for (int h = 0; h < 4; h++) {
            m[h][0] = fmaxf(m[h][0], __shfl_xor_sync(0xffffffffu, m[h][0], o));
            m[h][1] = fmaxf(m[h][1], __shfl_xor_sync(0xffffffffu, m[h][1], o));
        }
    }
}
__device__ __forceinline__ void attn_exp(const Ctx& c, float (&s)[4][4], float (&m)[4][2]) {
    constexpr float kf = SILU_TANH ? 2.f * kScale : -kScale / 1.4426950408889634f;
    const float k0 = kf * c.ga0, k1 = kf * c.ga1;
#pragma unroll
    for (int h = 0; h < 4; h++) {
        const float m0 = m[h][0] * -k0, m1 = m[h][1] * -k1;
        s[h][0] = ex2(fmaf(s[h][0], k0, m0)); s[h][1] = ex2(fmaf(s[h][1], k0, m0));
        s[h][2] = ex2(fmaf(s[h][2], k1, m1)); s[h][3] = ex2(fmaf(s[h][3], k1, m1));
        m[h][0] = s[h][0] + s[h][1]; m[h][1] = s[h][2] + s[h][3];
    }
}
__device__ __forceinline__ void attn_sum(float (&m)[4][2]) {
#pragma unroll
    for (int o = 1; o < 4; o <<= 1) {
#pragma unroll
        for (int h = 0; h < 4; h++) {
            m[h][0] += __shfl_xor_sync(0xffffffffu, m[h][0], o);
            m[h][1] += __shfl_xor_sync(0xffffffffu, m[h][1], o);
        }
    }
#pragma unroll
    for (int h = 0; h < 4; h++) { m[h][0] = rcp(m[h][0]); m[h][1] = rcp(m[h][1]); }
}
__device__ __forceinline__ void attn_probs(const Ctx& c, const float (&s)[4][4], const float (&m)[4][2], uint32_t (&p)[4][4]) {
    const uint32_t mk = ((2 * c.q > c.g) ? 0x0000ffffu : 0u) | ((2 * c.q + 1 > c.g) ? 0xffff0000u : 0u);
#pragma unroll
    for (int h = 0; h < 4; h++) {
        const uint32_t lo = pack2(s[h][0] * m[h][0], s[h][1] * m[h][0]), hi = pack2(s[h][2] * m[h][1], s[h][3] * m[h][1]);
        p[h][0] = andv(lo, mk); p[h][1] = andv(lo, ~mk); p[h][2] = andv(hi, mk); p[h][3] = andv(hi, ~mk);
    }
}
template <int I0, int I1, int N>
__device__ __forceinline__ void transpose_frags(uint32_t (&v)[N]) {
#pragma unroll
    for (int i = I0; i < I1; i++) v[i] = movm(v[i]);
}
template <int H>
__device__ __forceinline__ void attn_pv(const uint32_t (&p)[4], const uint32_t (&vp)[20], const uint32_t (&hv)[10], float (&o)[3][4]) {
    constexpr int GA = (H == 0) ? 0 : (H == 1) ? 3 : (H == 2) ? 5 : 8;
    constexpr int GS = (H < 2) ? 2 : 7;
#pragma unroll
    for (int t = 0; t < 3; t++) {
        const int G = (t < 2) ? GA + t : GS;
        mma16v(o[t], p[0], 0u, p[1], p[2], hv[G], vp[2 * G], 0.f, 0.f, 0.f, 0.f);
        mma8v(o[t], 0u, p[3], vp[2 * G + 1]);
    }
}
template <int H>
__device__ __forceinline__ void attn_pv_pack(const Ctx& c, const uint32_t (&p)[4], const uint32_t (&vp)[20], const uint32_t (&hv)[10], uint32_t (&op)[20]) {
    constexpr int GA = (H == 0) ? 0 : (H == 1) ? 3 : (H == 2) ? 5 : 8;
    constexpr int GS = (H < 2) ? 2 : 7;
    float o[3][4];
    attn_pv<H>(p, vp, hv, o);
#pragma unroll
    for (int t = 0; t < 2; t++) { op[2 * (GA + t)] = pack2(o[t][0], o[t][1]); op[2 * (GA + t) + 1] = pack2(o[t][2], o[t][3]); }
    const uint32_t lo = pack2(o[2][0], o[2][1]), hi = pack2(o[2][2], o[2][3]);
    if ((H & 1) == 0) { op[2 * GS] = lo; op[2 * GS + 1] = hi; }
    else { op[2 * GS] = (c.q >= 2) ? lo : op[2 * GS]; op[2 * GS + 1] = (c.q >= 2) ? hi : op[2 * GS + 1]; }
}
__device__ __forceinline__ void attn_pack(const Ctx& c, const float (&o)[4][3][4], uint32_t (&op)[20]) {
#pragma unroll
    for (int h = 0; h < 4; h++) {
        const int GA = (h == 0) ? 0 : (h == 1) ? 3 : (h == 2) ? 5 : 8;
#pragma unroll
        for (int t = 0; t < 2; t++) { op[2 * (GA + t)] = pack2v(o[h][t][0], o[h][t][1]); op[2 * (GA + t) + 1] = pack2v(o[h][t][2], o[h][t][3]); }
    }
    const bool even = c.q < 2;
#pragma unroll
    for (int hp = 0; hp < 2; hp++) {
        const int GS = hp ? 7 : 2;
        const float* e = o[2 * hp][2];
        const float* d = o[2 * hp + 1][2];
        op[2 * GS] = pack2v(even ? e[0] : d[0], even ? e[1] : d[1]);
        op[2 * GS + 1] = pack2v(even ? e[2] : d[2], even ? e[3] : d[3]);
    }
}

__device__ __forceinline__ void swiglu_consts(Ctx& c, float r0, float r1) {
    c.ga0 = 0.5f * r0; c.ga1 = 0.5f * r1; c.gb0 = c.ga0 * r0; c.gb1 = c.ga1 * r1;
}
__device__ __forceinline__ uint32_t piece_off() {
    const uint32_t t = launder(threadIdx.x);
    const uint32_t row = (t >> 7) * 64 + ((t >> 5) & 3) * 16 + ((t & 31) >> 2);
    return row * 64 + (((t & 3) ^ ((row >> 1) & 3)) << 4);
}
#define PIECE_OFF(c) ((c).aoff)
__device__ __forceinline__ uint8_t* act_piece(const Ctx& c, int tile) { return g_act + (size_t)tile * (34 * 16384) + PIECE_OFF(c); }
__device__ __forceinline__ void stg128(uint8_t* p, uint32_t a, uint32_t b, uint32_t c, uint32_t d) {
    asm volatile("st.global.v4.b32 [%0], {%1, %2, %3, %4};" ::"l"(p), "r"(a), "r"(b), "r"(c), "r"(d) : "memory");
}
__device__ __forceinline__ void stg64(uint8_t* p, uint32_t a, uint32_t b) {
    asm volatile("st.global.v2.b32 [%0], {%1, %2};" ::"l"(p), "r"(a), "r"(b) : "memory");
}

__device__ __forceinline__ void o_store(const Ctx& c, int tile, int slot, const uint32_t (&op)[20]) {
    uint8_t* odst = act_piece(c, tile) + 5 * (slot >> 1) * 8192;
    if ((slot & 1) == 0) {
        stg128(odst, op[0], op[2], op[4], op[6]);
        stg128(odst + 512, op[1], op[3], op[5], op[7]);
        stg128(odst + 8192, op[8], op[10], op[12], op[14]);
        stg128(odst + 8192 + 512, op[9], op[11], op[13], op[15]);
        stg64(odst + 16384, op[16], op[18]);
        stg64(odst + 16384 + 512, op[17], op[19]);
    } else {
        stg64(odst + 16384 + 8, op[0], op[2]);
        stg64(odst + 16384 + 512 + 8, op[1], op[3]);
        stg128(odst + 24576, op[4], op[6], op[8], op[10]);
        stg128(odst + 24576 + 512, op[5], op[7], op[9], op[11]);
        stg128(odst + 32768, op[12], op[14], op[16], op[18]);
        stg128(odst + 32768 + 512, op[13], op[15], op[17], op[19]);
    }
}

__device__ __forceinline__ void swiglu_group(const Ctx& c, const float (&acc)[64], int G, const float2 cg, const float2 cu, uint32_t& lo, uint32_t& hi) {
    float h[4];
#pragma unroll
    for (int e = 0; e < 4; e++) {
        const float m = (e < 2) ? c.m0 : c.m1, ga = (e < 2) ? c.ga0 : c.ga1, gb = (e < 2) ? c.gb0 : c.gb1;
        const float gate = fmaf(m, (e & 1) ? cg.y : cg.x, acc[4 * G + e]), up = fmaf(m, (e & 1) ? cu.y : cu.x, acc[32 + 4 * G + e]);
        h[e] = (gate * up) * fmaf(tanh_fast(gate * ga), gb, gb);
    }
    lo = pack2(h[0], h[1]);
    hi = pack2(h[2], h[3]);
}
template <int F, int G0, int G1>
__device__ __forceinline__ void swiglu_pre(const Ctx& c, float2 (&cs)[8]) {
#pragma unroll
    for (int G = G0; G < G1; G++) {
        cs[2 * (G - G0)] = lds64(c.sb + sm_csb(F) + (8 * G + 2 * c.q) * 4);
        cs[2 * (G - G0) + 1] = lds64(c.sb + sm_csb(F) + 256 + (8 * G + 2 * c.q) * 4);
    }
}
template <int F, int G0, int G1, int NPRE>
__device__ __forceinline__ void swiglu_groups(const Ctx& c, const float (&acc)[64], const float2 (&cs)[8], uint32_t (&hp)[8], uint8_t* hdst,
                                              uint32_t sdst = 0) {
#pragma unroll
    for (int G = G0; G < G1; G++) {
        const float2 cg = (G - G0 < NPRE) ? cs[2 * (G - G0)] : lds64(c.sb + sm_csb(F) + (8 * G + 2 * c.q) * 4);
        const float2 cu = (G - G0 < NPRE) ? cs[2 * (G - G0) + 1] : lds64(c.sb + sm_csb(F) + 256 + (8 * G + 2 * c.q) * 4);
        swiglu_group(c, acc, G, cg, cu, hp[G & 3], hp[4 + (G & 3)]);
        if ((G & 3) == 3) {
            if (F >= 1) {
                sts128(sdst + (G >> 2) * 8192, make_uint4(hp[0], hp[1], hp[2], hp[3]));
                sts128(sdst + (G >> 2) * 8192 + 512, make_uint4(hp[4], hp[5], hp[6], hp[7]));
            } else {
                stg128(hdst + (G >> 2) * 8192, hp[0], hp[1], hp[2], hp[3]);
                stg128(hdst + (G >> 2) * 8192 + 512, hp[4], hp[5], hp[6], hp[7]);
            }
        }
    }
}
template <int F>
__device__ __forceinline__ uint32_t own_piece(const Ctx& c) { return c.sb + (F == 1 ? SM_X : SM_OWN) + PIECE_OFF(c); }
template <int F>
__device__ __forceinline__ void own_done(const Ctx& c) {
    asm volatile("fence.proxy.async.shared::cta;" ::: "memory");
    arrive_local(c, B_WDONE + 1 + F);
}

template <int N>
__device__ __forceinline__ void f_issue(const Ctx& c, float (&acc)[64]) {
    constexpr int S = (N - 20) % 10, SLOT = N & 3;
    if (threadIdx.x < 32) TRACEF(192 + N);
    mbar_wait(c.bar + (B_RFULL + SLOT) * 8, (N >> 2) & 1);
    if (threadIdx.x < 32) TRACEF(64 + N);
    wg_fence();
#pragma unroll
    for (int kk = 0; kk < 4; kk++)
        wgmma_n128(acc, c.a_lo + S * 1024 + kk * 2, HI_128, c.b_lo + lbo(8192) + SLOT * 1024 + kk * 128, HI_128, (S | kk) != 0);
    wg_commit();
    wg_wait<1>();
    if (N - 1 <= 45) arrive_both(c, B_REMPTY + ((N - 1) & 3));
    if (N == 43) { mbar_wait(c.bar + B_INIT * 8, 0); arrive_both(c, B_GEMPTY + 0); }
    if (N == 45) arrive_both(c, B_GEMPTY + 1);
    if (N == 48) arrive_both(c, B_GEMPTY + 2);
}

template <bool RF>
__device__ __forceinline__ void q_epilogue(const Ctx& c, float2 (&cs)[8], const float (&q1)[96], const float (&q2)[24], uint32_t (&qp)[20],
                                           uint32_t (&kp)[20], uint32_t (&vp)[20], float (&accA)[64], bool hst, uint8_t* hq_st) {
    qkv_pre<RF, 0, 4>(c, cs);   f_issue<23>(c, accA); qkv_pack<RF, 0, 4>(c, cs, q1, q2, qp, kp, vp);
    qkv_pre<RF, 4, 8>(c, cs);   f_issue<24>(c, accA); qkv_pack<RF, 4, 8>(c, cs, q1, q2, qp, kp, vp);
    if (hst) stg128(hq_st, kp[1], kp[3], kp[7], kp[9]);
    qkv_pre<RF, 8, 12>(c, cs);  f_issue<25>(c, accA); qkv_pack<RF, 8, 12>(c, cs, q1, q2, qp, kp, vp);
    if (hst) { stg128(hq_st + 512, kp[11], kp[13], kp[17], kp[19]); stg128(hq_st + 1024, kp[5], kp[15], vp[1], vp[3]); }
    qkv_pre<RF, 12, 16>(c, cs); f_issue<26>(c, accA); qkv_pack<RF, 12, 16>(c, cs, q1, q2, qp, kp, vp);
    if (hst) stg128(hq_st + 1536, vp[5], vp[7], vp[9], vp[11]);
    qkv_pre<RF, 16, 20>(c, cs); f_issue<27>(c, accA); qkv_pack<RF, 16, 20>(c, cs, q1, q2, qp, kp, vp);
    if (hst) stg128(hq_st + 2048, vp[13], vp[15], vp[17], vp[19]);
    __syncwarp();
    if (c.lane == 0) {
        mbar_arrive(c.bar + (B_HALOR + c.par) * 8);
        if (c.w == 3) mbar_arrive(c.bar + B_HALOW * 8);
    }
    qkv_pre<RF, 20, 25>(c, cs); f_issue<28>(c, accA); qkv_pack<RF, 20, 25>(c, cs, q1, q2, qp, kp, vp);
    transpose_frags<0, 10>(vp);
    qkv_pre<RF, 25, 30>(c, cs); arrive_local(c, B_CSFREE); f_issue<29>(c, accA); qkv_pack<RF, 25, 30>(c, cs, q1, q2, qp, kp, vp);
    transpose_frags<10, 20>(vp);
}

__device__ __forceinline__ void block_edge(const Ctx& c) { mbar_wait(c.bar + B_CS * 8, 0); }

struct AccG {
    float v[80];
    __device__ __forceinline__ float operator[](int i) const { return v[i]; }
};
__device__ __forceinline__ void g_issue(const Ctx& c, AccG& acc, int slot, int parity, bool first, int t, bool own = false) {
    if (threadIdx.x < 32) TRACEFG(250 + t);
    if (first) mbar_wait(c.bar + (B_WDONE + 2) * 8, 0);
    if (own) mbar_wait(c.bar + (B_WDONE + 3) * 8, 0);
    mbar_wait(c.bar + (B_GFULL + slot) * 8, parity);
    if (threadIdx.x < 32) TRACEFG(120 + t);
    wg_fence();
    const uint32_t s0 = (c.sb & 0x3FFFF) >> 4, st = s0 + slot * (G_STAGE >> 4);
    const uint32_t alo = (own ? s0 + (SM_OWN >> 4) : st) + c.par * 256 + lbo(16), blo = st + 1024 + lbo(4096);
#pragma unroll
    for (int kk = 0; kk < 4; kk++) {
        wgmma_n160(acc.v, alo + (kk >> 1) * 512 + (kk & 1) * 2, HI_64, blo + (kk >> 1) * 768 + (kk & 1) * 128, HI_128, !(first && kk == 0));
    }
    wg_commit();
}

template <int N, int BIT, int M>
__device__ __forceinline__ void halve(float (&acc)[M], int lane) {
    const bool up = lane & BIT;
#pragma unroll
    for (int e = 0; e < N; e++) {
        const float lo = acc[e], hi = acc[e + N];
        const float send = up ? lo : hi, keep = up ? hi : lo;
        acc[e] = keep + __shfl_xor_sync(0xffffffffu, send, BIT);
    }
}
template <int O, int M>
__device__ __forceinline__ void acc8(float (&acc)[M], const uint4& v) {
    acc[O + 0] += bf_lo(v.x); acc[O + 1] += bf_hi(v.x); acc[O + 2] += bf_lo(v.y); acc[O + 3] += bf_hi(v.y);
    acc[O + 4] += bf_lo(v.z); acc[O + 5] += bf_hi(v.z); acc[O + 6] += bf_lo(v.w); acc[O + 7] += bf_hi(v.w);
}
__device__ __forceinline__ uint4 ldg_nc(const void* p) {
    uint4 v; asm volatile("ld.global.nc.v4.u32 {%0,%1,%2,%3}, [%4];" : "=r"(v.x), "=r"(v.y), "=r"(v.z), "=r"(v.w) : "l"(p)); return v;
}

constexpr uint32_t H_BUF = 32768, H_RED = 6 * H_BUF;
constexpr int H_FULL = 0, H_EMPTY = 6;
__device__ __forceinline__ uint4 f4_bits(float a, float b, float c, float d) {
    return make_uint4(__float_as_uint(a), __float_as_uint(b), __float_as_uint(c), __float_as_uint(d));
}
__device__ __forceinline__ void helper_cta(int h, uint32_t sb, const Maps& maps, const __nv_bfloat16* wqkv,
                                           const __nv_bfloat16* wo, const __nv_bfloat16* w2) {
    const int t = threadIdx.x, warp = __shfl_sync(0xffffffffu, t >> 5, 0), lane = t & 31;
    const uint32_t bar = sb + SM_BAR;
    if (t == 0) {
        for (int i = 0; i < 6; i++) { mbar_init(bar + (H_FULL + i) * 8, 1); mbar_init(bar + (H_EMPTY + i) * 8, 8); }
        asm volatile("fence.mbarrier_init.release.cluster;" ::: "memory");
    }
    __syncthreads();
    if (warp == 11) {
        const CUtensorMap* mc = (h >> 1) ? &maps.w3c : &maps.w1c;
        int s = 0, ph = 1;
#pragma unroll 1
        for (int i = 0; i < 50; i++) {
            mbar_wait(bar + (H_EMPTY + s) * 8, ph);
            if (elect_one()) {
                if (i < 20) {
                    mbar_expect_tx(bar + (H_FULL + s) * 8, 32768);
                    tma2(sb + s * H_BUF, &maps.wqc, 512 * h + 256 * (i & 1), 64 * (JOBA_REV ? 9 - (i >> 1) : (i >> 1)), bar + (H_FULL + s) * 8);
                } else {
                    const int f = (i - 20) / 10, r = (i - 20) % 10;
                    mbar_expect_tx(bar + (H_FULL + s) * 8, 32768);
                    tma2(sb + s * H_BUF, mc, 512 * f + 256 * (r & 1), 320 * (h & 1) + 64 * (r >> 1), bar + (H_FULL + s) * 8);
                }
            }
            if (++s == 6) { s = 0; ph ^= 1; }
        }
        return;
    }
    if (warp >= 8) return;
    const unsigned tag = ld_relaxed(&g_cntO[0]) / 8 + 1;
    int s = 0, ph = 0;
#pragma unroll 1
    for (int job = 0; job < 4; job++) {
        float acc[2][8];
#pragma unroll
        for (int e = 0; e < 8; e++) acc[0][e] = acc[1][e] = 0.f;
#pragma unroll 1
        for (int rb = 0; rb < (job ? 5 : 10); rb++) {
#pragma unroll
            for (int ch = 0; ch < 2; ch++) {
                mbar_wait(bar + (H_FULL + s) * 8, ph);
                uint4 v[8];
#pragma unroll
                for (int r = 0; r < 8; r++) v[r] = lds128(sb + s * H_BUF + (warp * 8 + r) * 512 + lane * 16);
#pragma unroll
                for (int r = 0; r < 8; r++) acc8<0>(acc[ch], v[r]);
                __syncwarp();
                if (lane == 0) mbar_arrive(bar + (H_EMPTY + s) * 8);
                if (++s == 6) { s = 0; ph ^= 1; }
            }
        }
#pragma unroll
        for (int ch = 0; ch < 2; ch++) {
            sts128(sb + H_RED + (warp * 512 + ch * 256 + lane * 8) * 4, f4_bits(acc[ch][0], acc[ch][1], acc[ch][2], acc[ch][3]));
            sts128(sb + H_RED + (warp * 512 + ch * 256 + lane * 8 + 4) * 4, f4_bits(acc[ch][4], acc[ch][5], acc[ch][6], acc[ch][7]));
        }
        bar_sync<1, 256>();
        {
            float s0 = 0.f, s1 = 0.f;
#pragma unroll
            for (int r = 0; r < 8; r++) { const float2 v = lds64(sb + H_RED + (r * 512 + 2 * t) * 4); s0 += v.x; s1 += v.y; }
            if (job == 0) { if (512 * h + 2 * t < 1920) st_tag2(&g_csA[512 * h + 2 * t], tagged(tag, s0), tagged(tag, s1)); }
            else st_tag2(&g_csB[((h & 1) * 2 + (h >> 1)) * kF + 512 * (job - 1) + 2 * t], tagged(tag, s0), tagged(tag, s1));
        }
        bar_sync<1, 256>();
        if (warp == 0) TRACE(job == 0 ? 25 : 29 + job);
    }
#pragma unroll 1
    for (int k = h * 256 + t; k < 6400 + 15360; k += 4 * 256) {
        const __nv_bfloat16* p = (k < 6400) ? wo + (size_t)k * 64 : w2 + (size_t)(k - 6400) * 64;
        asm volatile("prefetch.global.L2 [%0];" ::"l"(p));
    }
}

}

__global__ void __cluster_dims__(2, 1, 1) __launch_bounds__(384, 1)
fused_block_kernel(const __grid_constant__ Maps maps, const __nv_bfloat16* __restrict__ x, const __nv_bfloat16* __restrict__ wqkv,
                   const __nv_bfloat16* __restrict__ w1, const __nv_bfloat16* __restrict__ w3,
                   const __nv_bfloat16* __restrict__ wo, const __nv_bfloat16* __restrict__ w2, __nv_bfloat16* __restrict__ out) {
    extern __shared__ __align__(1024) uint8_t smem_raw[];
    const uint32_t sb = smem_u32(smem_raw);
    const int warp = __shfl_sync(0xffffffffu, threadIdx.x >> 5, 0);
    const int lane = threadIdx.x & 31;
    uint32_t rank;
    asm("mov.u32 %0, %%cluster_ctarank;" : "=r"(rank));
    const int b = blockIdx.x;
    if (b >= 128) {
        if (threadIdx.x == 0) TRACE(0);
        helper_cta(b - 128, sb, maps, wqkv, wo, w2);
        return;
    }
    const int pair = b >> 1;
    const int slot = (pair + SLOT_ROT) & 7;
    const int tile = (pair >> 3) * 2 + rank;
    const int jj = slot >> 1;
    const int half = (slot ^ (slot >> 1)) & 1;
    const int own_i = 2 * (slot >> 2) + ((slot & 3) >> 1);
    auto hslot = [&](int i) { return 4 * ((i >> 1) & 1) + (half ? 1 + (i & 1) : 3 * (i & 1)); };
    const bool rf = RF_ALIGN && (slot & 3) == 3;
    const int wcol = 80 * slot + (rf ? 16 : 0), wcolr = 80 * slot + (rf ? 0 : 64);

    if (threadIdx.x == 0) TRACE(0);
    if (warp == 8) {
        TRACEG(62);
        if (elect_one()) {
#pragma unroll
            for (int i = 0; i < B_GFULL; i++) mbar_init(sb + SM_BAR + i * 8, bar_count(i));
            asm volatile("fence.mbarrier_init.release.cluster;" ::: "memory");
        }
        TRACE(22);
    } else if (warp == 9) {
        if (elect_one()) {
            prefetch_map(&maps.x); prefetch_map(&maps.wq); prefetch_map(&maps.wqr);
#pragma unroll
            for (int i = B_GFULL; i < B_CSFREE; i++) mbar_init(sb + SM_BAR + i * 8, bar_count(i));
            asm volatile("fence.mbarrier_init.release.cluster;" ::: "memory");
        }
    } else if (warp == 10) {
        if (elect_one()) {
#pragma unroll
            for (int i = B_CSFREE; i < B_COUNT; i++) mbar_init(sb + SM_BAR + i * 8, bar_count(i));
            asm volatile("fence.mbarrier_init.release.cluster;" ::: "memory");
        }
    }
    __syncthreads();
    if (warp == 8) TRACE(23);
    asm volatile("barrier.cluster.arrive.relaxed.aligned;" ::: "memory");
    if (warp == 8) {
        if (elect_one()) {
            mbar_expect_tx(sb + SM_BAR + B_XFULL * 8, 16384);
            tma3(sb + SM_X, &maps.x, 0, tile * 64, 0, sb + SM_BAR + B_XFULL * 8);
        }
        __syncwarp();
    }
    asm volatile("barrier.cluster.wait.aligned;" ::: "memory");
    if (warp == 8) {
        TRACE(24);
        if (elect_one()) {
#pragma unroll
            for (int n = 0; n < 4; n++) {
                const uint32_t fb = sb + SM_BAR + (B_RFULL + n) * 8;
                mbar_expect_tx(fb, 15360);
                tma3_mc(sb + SM_RING + n * 16384 + rank * 6144, &maps.wq, wcol, 32 * n + 16 * rank, 0, fb);
                tma3_mc(sb + SM_RING + n * 16384 + 12288 + rank * 1536, &maps.wqr, wcolr, 32 * n + 16 * rank, 0, fb);
                if (n & 1) {
                    const int c = (n + 1) / 2;
                    mbar_expect_tx(sb + SM_BAR + (B_XFULL + c) * 8, 16384);
                    tma3(sb + SM_X + c * 16384, &maps.x, c * 64, tile * 64, 0, sb + SM_BAR + (B_XFULL + c) * 8);
                }
            }
        }
        __syncwarp();
        TRACE(1);
    }
    unsigned cnt0 = 0;
    if (warp > 8) cnt0 = ld_relaxed(&g_cntO[tile * 32]);

    if (warp >= 8) {
        asm volatile("setmaxnreg.dec.sync.aligned.u32 56;");
        const uint32_t bar = launder(sb + SM_BAR);
        const int n0 = half ? 8 - NH0 : NH0;
        auto g_load = [&](int t, int s, int ph, int part) {
            const int u = t - 1 - n0;
            const int kc = (t == 0) ? 18 + slot : (u < 0) ? 10 + NH0 * half + t - 1 : (u < 5) ? 5 * half + u
                         : (u < 8) ? 18 + hslot(own_i + u - 4) : 26 + hslot(own_i + u - 8);
            const int flag = (t == 1) ? 0 : (u == 0) ? 1 : (u >= 5 && u < 8) ? u - 3 : (u >= 9) ? u - 4 : -1;
            const bool own = (t == 0) || (u == 8);
            const uint32_t st = sb + s * G_STAGE, fb = bar + (B_GFULL + s) * 8;
            if (part & 1) {
                mbar_wait(bar + (B_GEMPTY + s) * 8, ph);
                TRACEP(280 + t);
                if (elect_one()) {
                    const bool isO = kc < 10;
                    const int a0 = ((isO ? kc : kc - 10) * 2 + rank) * 4;
                    mbar_expect_tx(fb, own ? 20480 : 16384 + 20480);
                    tma5_mc(st + 16384 + rank * 12288, isO ? &maps.wo2 : &maps.w22, 160 * jj + G_ALIGN * 32 * (jj & 1), a0, fb);
                    tma4_mc(st + 16384 + rank * 12288 + 8192, isO ? &maps.wo1 : &maps.w21, 160 * jj + ((G_ALIGN && (jj & 1)) ? 0 : 128), a0, fb);
                }
            }
            if ((part & 2) && !own) {
                if (flag >= 0) mbar_wait(bar + (B_FLAG + flag) * 8, 0);
                if (t == 5) mbar_wait(bar + B_H1OUT * 8, 0);
                TRACEP(300 + t);
                if (elect_one()) bulk_g2s(st, g_act + (size_t)(tile * 34 + kc) * 16384, 16384, fb);
            }
        };
        if (warp == 8) {
            const uint32_t ring = launder(sb + SM_RING);
#pragma unroll 1
            for (int n = 4; n < 20; n++) {
                const int s = n & 3;
                mbar_wait(bar + (B_REMPTY + s) * 8, ((n >> 2) - 1) & 1);
                TRACEP(140 + n);
                const int c = (n == 4) ? 3 : (n <= 15 && (n & 1)) ? (n + 3) / 2 : 0;
                if (elect_one()) {
                    mbar_expect_tx(bar + (B_RFULL + s) * 8, 15360);
                    tma3_mc(ring + s * 16384 + rank * 6144, &maps.wq, wcol, 32 * n + 16 * rank, 0, bar + (B_RFULL + s) * 8);
                    tma3_mc(ring + s * 16384 + 12288 + rank * 1536, &maps.wqr, wcolr, 32 * n + 16 * rank, 0, bar + (B_RFULL + s) * 8);
                    if (c > 0) {
                        mbar_expect_tx(bar + (B_XFULL + c) * 8, 16384);
                        tma3(sb + SM_X + c * 16384, &maps.x, c * 64, tile * 64, 0, bar + (B_XFULL + c) * 8);
                    }
                }
            }
            const CUtensorMap* mf = rank ? &maps.w3 : &maps.w1;
            {
                int col = 64 * slot, k = 0;
#pragma unroll 1
                for (int n = 20; n < 50; n++) {
                    const int s = n & 3;
                    mbar_wait(bar + (B_REMPTY + s) * 8, ((n >> 2) - 1) & 1);
                    TRACEP(140 + n);
                    if (elect_one()) {
                        mbar_expect_tx(bar + (B_RFULL + s) * 8, 16384);
                        tma2_mc(ring + s * 16384 + rank * 8192, mf, col, k, bar + (B_RFULL + s) * 8);
                    }
                    k += 64;
                    if (k == 640) { k = 0; col += 512; }
                }
            }
            TRACE(2);
            constexpr int T1 = 2;
            int s = T1, ph = 0;
            const int nt = 13 + n0;
#pragma unroll 1
            for (int t = T1; t < nt; t++) {
                g_load(t, s, ph, 3);
                if (++s == 5) { s = 0; ph ^= 1; }
            }
            TRACE(3);
        } else {
            const int a = warp - 9;
            const unsigned tag = cnt0 / 8 + 1;
            if (a == 0) {
                mbar_wait(bar + (B_XFULL + CS_WAIT) * 8, 0);
                {
                    const int n0 = 4 * lane, n1 = 128 + 4 * (lane < 28 ? lane : 27);
                    const unsigned* p0 = &g_csA[(n0 >> 6) * kD + wcol + (n0 & 63)];
                    const unsigned* p1 = &g_csA[(n1 < 192) ? 2 * kD + wcol + (n1 & 63) : ((n1 - 192) >> 4) * kD + wcolr + ((n1 - 192) & 15)];
                    uint4 v0, v1;
                    gather2(p0, p1, tag, v0, v1);
                    sts128(sb + SM_CS + lane * 16, f4_bits(tag_val(v0.x), tag_val(v0.y), tag_val(v0.z), tag_val(v0.w)));
                    if (lane < 28) sts128(sb + SM_CS + 512 + lane * 16, f4_bits(tag_val(v1.x), tag_val(v1.y), tag_val(v1.z), tag_val(v1.w)));
                    __syncwarp();
                    if (lane == 0) mbar_arrive(bar + B_CS * 8);
                }
                TRACE(5);
                mbar_wait(bar + B_HALOW * 8, 0);
                if (lane == 0) {
                    if (tile < 15) { fence_gpu(); st_relaxed(&g_flagHalo[(tile * 8 + slot) * 32], tag); }
                    if (tile > 0) poll_ge(&g_flagHalo[((tile - 1) * 8 + slot) * 32], tag);
                    mbar_arrive(bar + B_HALOR * 8);
                    mbar_arrive(bar + (B_HALOR + 1) * 8);
                    TRACE(28);
                }
                __syncwarp();
                poll_multi(&g_cntH[tile * 32], tag * 8, bar + (B_FLAG + 0) * 8, lane == 0); TRACE(44);
                const unsigned* fl = &g_flagH[(tile * 8 + hslot(own_i + lane + 1)) * 32];
                poll_multi(lane < 3 ? fl : &g_cntO[tile * 32], lane < 3 ? tag : tag * 8, bar + (lane < 3 ? B_FLAG + 2 + lane : B_FLAG + 1) * 8, lane < 4);
                TRACE(45); TRACE(46); TRACEG(50);
                poll_multi(fl + 16 * 8 * 32, tag, bar + (B_FLAG + 5 + (lane & 3)) * 8, lane < 3);
                TRACE(47); TRACEG(53);
            } else {
                {
                    const int t = 16 * slot + 8 * (a - 1) + (lane >> 2);
                    const uint32_t rowa = sb + SM_X + ((t & 1) * 64 + (t >> 1)) * 128 + (lane & 3) * 32;
                    float x0 = 0.f, s4[4] = {0.f, 0.f, 0.f, 0.f}, q4[4] = {0.f, 0.f, 0.f, 0.f};
#pragma unroll 1
                    for (int c = 0; c < 10; c++) {
                        mbar_wait(bar + (B_XFULL + c) * 8, 0);
                        const uint4 v0 = lds128(rowa + c * 16384), v1 = lds128(rowa + c * 16384 + 16);
                        if (c == 0) x0 = __shfl_sync(0xffffffffu, bf_lo(v0.x), lane & 28);
                        const uint32_t wv[8] = {v0.x, v0.y, v0.z, v0.w, v1.x, v1.y, v1.z, v1.w};
#pragma unroll
                        for (int e = 0; e < 8; e++) {
                            const float d0 = bf_lo(wv[e]) - x0, d1 = bf_hi(wv[e]) - x0;
                            s4[e & 3] += d0; q4[e & 3] = fmaf(d0, d0, q4[e & 3]);
                            s4[e & 3] += d1; q4[e & 3] = fmaf(d1, d1, q4[e & 3]);
                        }
                    }
                    float ss = (q4[0] + q4[1]) + (q4[2] + q4[3]), sm = (s4[0] + s4[1]) + (s4[2] + s4[3]);
#pragma unroll
                    for (int o = 1; o < 4; o <<= 1) { sm += __shfl_xor_sync(0xffffffffu, sm, o); ss += __shfl_xor_sync(0xffffffffu, ss, o); }
                    if ((lane & 3) == 0) {
                        const float dm = sm * (1.f / kD), var = fmaxf(ss * (1.f / kD) - dm * dm, 0.f);
                        st_tag2(&g_stats[(tile * 128 + t) * 2], tagged(tag, rsqrtf(var + 1e-5f)), tagged(tag, x0 + dm));
                    }
                    if (a == 1) TRACE(26);
                }
                if (a == 2) {
                    uint4 v0, v1;
                    gather2(&g_stats[(tile * 128 + 2 * lane) * 2], &g_stats[(tile * 128 + 64 + 2 * lane) * 2], tag, v0, v1);
                    asm volatile("st.shared.v2.f32 [%0], {%1,%2};" ::"r"(sb + SM_ST + lane * 8), "f"(tag_val(v0.x)), "f"(-tag_val(v0.y)) : "memory");
                    asm volatile("st.shared.v2.f32 [%0], {%1,%2};" ::"r"(sb + SM_ST + (64 + lane) * 8), "f"(tag_val(v0.z)), "f"(-tag_val(v0.w)) : "memory");
                    asm volatile("st.shared.v2.f32 [%0], {%1,%2};" ::"r"(sb + SM_ST + (32 + lane) * 8), "f"(tag_val(v1.x)), "f"(-tag_val(v1.y)) : "memory");
                    asm volatile("st.shared.v2.f32 [%0], {%1,%2};" ::"r"(sb + SM_ST + (96 + lane) * 8), "f"(tag_val(v1.z)), "f"(-tag_val(v1.w)) : "memory");
                    __syncwarp();
                    if (lane == 0) mbar_arrive(bar + B_ST * 8);
                    TRACE(6);
#pragma unroll 1
                    for (int r = 0; r < 2; r++) {
                        mbar_wait(bar + (B_WDONE + r) * 8, 0);
                        TRACE(36 + r);
                        if (lane == 0) { fence_gpu(); red_add(r ? &g_cntO[tile * 32] : &g_cntH[tile * 32], 1); }
                        __syncwarp();
                        TRACE(40 + r);
                    }
#pragma unroll 1
                    for (int r = 2; r < 4; r++) {
                        mbar_wait(bar + (B_WDONE + r) * 8, 0);
                        TRACE(36 + r); TRACEG(r == 2 ? 48 : 51);
                        if (elect_one()) {
                            asm volatile("cp.async.bulk.global.shared::cta.bulk_group [%0], [%1], %2;"
                                         ::"l"(g_act + (size_t)(tile * 34 + 2 + 8 * r + slot) * 16384), "r"(sb + (r == 2 ? SM_X : SM_OWN)), "r"(16384) : "memory");
                            asm volatile("cp.async.bulk.commit_group;" ::: "memory");
                            asm volatile("cp.async.bulk.wait_group 0;" ::: "memory");
                            st_relaxed(&g_flagH[((r - 2) * 128 + tile * 8 + slot) * 32], tag);
                            if (r == 2) mbar_arrive(bar + B_H1OUT * 8);
                        }
                        __syncwarp();
                        TRACE(40 + r); TRACEG(r == 2 ? 49 : 52);
                    }
                } else {
#pragma unroll 1
                    for (int f = 0; f < 3; f++) {
                        uint4 v, w;
                        int it = 0;
#pragma unroll 1
                        while (true) {
                            v = ld_tag4(&g_csB[(lane >> 4) * kF + 512 * f + 64 * slot + 4 * (lane & 15)]);
                            w = ld_tag4(&g_csB[(2 + (lane >> 4)) * kF + 512 * f + 64 * slot + 4 * (lane & 15)]);
                            if (__all_sync(0xffffffffu, tag_ok(v, tag) && tag_ok(w, tag)) || ++it > (1 << 15)) break;
                        }
                        if (f == 1) mbar_wait(bar + B_CSFREE * 8, 0);
                        sts128(sb + (f == 0 ? SM_CSB0 : SM_CS + (f - 1) * 512) + lane * 16,
                               f4_bits(tag_val(v.x) + tag_val(w.x), tag_val(v.y) + tag_val(w.y), tag_val(v.z) + tag_val(w.z), tag_val(v.w) + tag_val(w.w)));
                        __syncwarp();
                        if (lane == 0) mbar_arrive(bar + (B_CSB + f) * 8);
                        TRACE(33 + f);
                        if (f == 0) {
#pragma unroll 1
                            for (int i = 0; i < 10; i++) {
                                const int p = slot * 10 + i, xc = p >> 3, pi = p & 7;
                                if (elect_one()) tma3_store(&maps.o64, sb + SM_X + xc * 16384 + pi * 2048, 64 * xc, tile * 64 + 16 * (pi & 3), pi >> 2);
                                const long long t0 = clock64();
                                while (clock64() - t0 < INIT_GAP) { }
                            }
                            if (elect_one()) {
                                asm volatile("cp.async.bulk.commit_group;" ::: "memory");
                                asm volatile("cp.async.bulk.wait_group 0;" ::: "memory");
                                asm volatile("fence.proxy.async;" ::: "memory");
                                mbar_arrive(bar + (B_WDONE + 1) * 8);
                                mbar_arrive(bar + B_INIT * 8);
                            }
                            TRACE(7);
                        }
                    }
#pragma unroll 1
                    for (int i = 0; i < 4; i++) {
                        g_load(i >> 1, i >> 1, 0, 1 + (i & 1));
                        spin(G_AUX_GAP);
                    }
                }
            }
        }
    } else {
        asm volatile("setmaxnreg.inc.sync.aligned.u32 224;");
        Ctx c;
        c.sb = sb;
        c.bar = sb + SM_BAR;
        c.lane = lane; c.q = lane & 3; c.g = lane >> 2; c.w = warp & 3; c.par = warp >> 2;
        c.rbar = mapa(c.bar, lane & 1);
        c.a_lo = ((sb & 0x3FFFF) >> 4) + c.par * 512 + lbo(16);
        c.b_lo = ((sb + SM_RING) & 0x3FFFF) >> 4;
        const int idx0 = c.w * 16 + c.g;
        c.aoff = piece_off();

        float q1[96], q2[24];
#pragma unroll
        for (int n = 0; n < 20; n++) {
            if (warp == 0) TRACEF(192 + n);
            if ((n & 1) == 0) mbar_wait(c.bar + (B_XFULL + n / 2) * 8, 0);
            if ((n & 1) == 0 && warp == 0) TRACEF(270 + n / 2);
            if (n == 0 && warp == 0) TRACE(56);
            mbar_wait(c.bar + (B_RFULL + (n & 3)) * 8, (n >> 2) & 1);
            if (n == 0 && c.w == 0) TRACE(8 + c.par);
            if (n == 1 && warp == 0) TRACE(57);
            if (n == 2 && warp == 0) TRACE(58);
            if (n == 3 && warp == 0) TRACE(59);
            if (warp == 0) TRACEF(64 + n);
            wg_fence();
#pragma unroll
            for (int h = 0; h < 2; h++) {
                const uint32_t alo = c.a_lo + (n >> 1) * 1024 + ((n & 1) * 2 + h) * 2;
                wgmma_n192(q1, alo, HI_128, c.b_lo + lbo(2048) + (n & 3) * 1024 + h * 384, HI_128, (n | h) != 0);
                wgmma_n48(q2, alo, HI_128, c.b_lo + lbo(512) + (n & 3) * 1024 + 768 + h * 96, HI_32, (n | h) != 0);
            }
            wg_commit();
            wg_wait<1>();
            if (n > 0) arrive_both(c, B_REMPTY + ((n - 1) & 3));
        }
        if (c.w == 0) TRACE(10 + c.par);

        float accA[64], accB[64];
        uint32_t qp[20], kp[20], vp[20], hk[10], hv[10], op[20], hp[8];
        const bool first = (tile == 0) && (c.w == 0);
        float2 cs[8];
        f_issue<20>(c, accA);
        f_issue<21>(c, accA);
        f_issue<22>(c, accA);
        {
            mbar_wait(c.bar + B_ST * 8, 0);
            const float2 s0 = lds64(sb + SM_ST + (c.par * 64 + idx0) * 8), s1 = lds64(sb + SM_ST + (c.par * 64 + idx0 + 8) * 8);
            c.r0 = s0.x; c.m0 = s0.y; c.r1 = s1.x; c.m1 = s1.y;
            mbar_wait(c.bar + B_CS * 8, 0);
        }
        const int hdt = (c.w == 3) ? tile + 1 : tile;
        const bool hst = hdt < 16;
        uint8_t* hq_st = (uint8_t*)(g_halo + (size_t)(((hdt * 8 + slot) * 2 + c.par) * 4 + ((c.w + 1) & 3)) * 160 + lane);
        if (RF_ALIGN && (slot & 3) == 3) q_epilogue<true>(c, cs, q1, q2, qp, kp, vp, accA, hst, hq_st);
        else q_epilogue<false>(c, cs, q1, q2, qp, kp, vp, accA, hst, hq_st);
        swiglu_consts(c, c.r0, c.r1);
        if (c.w == 0) TRACE(12 + c.par);

        uint8_t* hdst = nullptr;
        mbar_wait(c.bar + B_CSB * 8, 0);
        swiglu_pre<0, 0, 2>(c, cs); f_issue<30>(c, accB); swiglu_groups<0, 0, 2, 2>(c, accA, cs, hp, hdst);
        swiglu_pre<0, 2, 3>(c, cs); f_issue<31>(c, accB); swiglu_groups<0, 2, 3, 1>(c, accA, cs, hp, hdst);
        hdst = act_piece(c, tile) + (10 + slot) * 16384;
        swiglu_pre<0, 3, 4>(c, cs); f_issue<32>(c, accB); swiglu_groups<0, 3, 4, 1>(c, accA, cs, hp, hdst);
        swiglu_pre<0, 4, 6>(c, cs); f_issue<33>(c, accB); swiglu_groups<0, 4, 6, 2>(c, accA, cs, hp, hdst);
        swiglu_pre<0, 6, 7>(c, cs); f_issue<34>(c, accB); swiglu_groups<0, 6, 7, 1>(c, accA, cs, hp, hdst);
        uint4 t0, t1, t2, t3, t4;
        {
            mbar_wait(c.bar + (B_HALOR + c.par) * 8, 0);
            const uint4* hq = g_halo + (size_t)(((tile * 8 + slot) * 2 + c.par) * 4 + c.w) * 160 + lane;
            t0 = __ldcg(hq); t1 = __ldcg(hq + 32); t2 = __ldcg(hq + 64); t3 = __ldcg(hq + 96); t4 = __ldcg(hq + 128);
        }
        hdst = act_piece(c, tile) + (10 + slot) * 16384;
        swiglu_pre<0, 7, 8>(c, cs); f_issue<35>(c, accB); swiglu_groups<0, 7, 8, 1>(c, accA, cs, hp, hdst);
        arrive_local(c, B_WDONE + 0);
        hk[0] = t0.x; hk[1] = t0.y; hk[3] = t0.z; hk[4] = t0.w; hk[5] = t1.x; hk[6] = t1.y; hk[8] = t1.z; hk[9] = t1.w;
        hk[2] = t2.x; hk[7] = t2.y; hv[0] = t2.z; hv[1] = t2.w; hv[2] = t3.x; hv[3] = t3.y; hv[4] = t3.z; hv[5] = t3.w;
        hv[6] = t4.x; hv[7] = t4.y; hv[8] = t4.z; hv[9] = t4.w;
        float sc[4][4], mx[4][2];
        uint32_t pr[4][4];
        {
            float lg[4][3][4], nq;
            uint32_t qs[4][2];
            attn_prep(c, first, qp, qs, nq);
            f_issue<36>(c, accB);
            block_edge(c);
            attn_logits<0>(qp, qs, kp, hk, nq, lg[0][0], lg[0][1], lg[0][2]); attn_logits<1>(qp, qs, kp, hk, nq, lg[1][0], lg[1][1], lg[1][2]);
            attn_logits<2>(qp, qs, kp, hk, nq, lg[2][0], lg[2][1], lg[2][2]); attn_logits<3>(qp, qs, kp, hk, nq, lg[3][0], lg[3][1], lg[3][2]);
            f_issue<37>(c, accB); attn_select(c, lg, sc); attn_max(sc, mx);
        }
        f_issue<38>(c, accB); attn_exp(c, sc, mx);
        f_issue<39>(c, accB); attn_sum(mx);
        if (c.w == 0) TRACE(14 + c.par);

        f_issue<40>(c, accA); attn_probs(c, sc, mx, pr);
        transpose_frags<0, 10>(hv);
        {
            float ov[4][3][4];
            f_issue<41>(c, accA);
            block_edge(c);
            attn_pv<0>(pr[0], vp, hv, ov[0]); attn_pv<1>(pr[1], vp, hv, ov[1]); attn_pv<2>(pr[2], vp, hv, ov[2]); attn_pv<3>(pr[3], vp, hv, ov[3]);
            f_issue<42>(c, accA); attn_pack(c, ov, op);
        }
        o_store(c, tile, slot, op);
        f_issue<43>(c, accA);
        arrive_local(c, B_WDONE + 1);
        mbar_wait(c.bar + (B_CSB + 1) * 8, 0);
        {
            const uint32_t sa = launder(sb + SM_ST + (c.par * 64 + idx0) * 8);
            const float2 s0 = lds64(sa), s1 = lds64(sa + 64);
            c.m0 = s0.y; c.m1 = s1.y;
            swiglu_consts(c, s0.x, s1.x);
        }
        swiglu_pre<1, 0, 2>(c, cs); f_issue<44>(c, accA); swiglu_groups<1, 0, 2, 2>(c, accB, cs, hp, nullptr, 0);
        swiglu_pre<1, 2, 4>(c, cs); f_issue<45>(c, accA); swiglu_groups<1, 2, 4, 2>(c, accB, cs, hp, nullptr, own_piece<1>(c));
        swiglu_pre<1, 4, 6>(c, cs); f_issue<46>(c, accA); swiglu_groups<1, 4, 6, 2>(c, accB, cs, hp, nullptr, 0);
        swiglu_pre<1, 6, 7>(c, cs); f_issue<47>(c, accA); swiglu_groups<1, 6, 7, 1>(c, accB, cs, hp, nullptr, 0);
        swiglu_pre<1, 7, 8>(c, cs); f_issue<48>(c, accA); swiglu_groups<1, 7, 8, 1>(c, accB, cs, hp, nullptr, own_piece<1>(c));
        own_done<1>(c);
        f_issue<49>(c, accA);
        if (c.w == 0) TRACE(16 + c.par);

        AccG accG;
        mbar_wait(c.bar + (B_CSB + 2) * 8, 0);
        swiglu_pre<2, 0, 4>(c, cs);
        wg_wait<0>();
        arrive_both(c, B_GEMPTY + 3);
        arrive_both(c, B_GEMPTY + 4);
        {
            const uint32_t sdst = own_piece<2>(c);
            swiglu_groups<2, 0, 4, 4>(c, accA, cs, hp, nullptr, sdst);
            swiglu_pre<2, 4, 8>(c, cs);
            swiglu_groups<2, 4, 8, 4>(c, accA, cs, hp, nullptr, sdst);
        }
        own_done<2>(c);
        g_issue(c, accG, 0, 0, true, 0);
        g_issue(c, accG, 1, 0, false, 1); wg_wait<1>(); arrive_both(c, B_GEMPTY + 0);
        g_issue(c, accG, 2, 0, false, 2); wg_wait<1>(); arrive_both(c, B_GEMPTY + 1);
        g_issue(c, accG, 3, 0, false, 3); wg_wait<1>(); arrive_both(c, B_GEMPTY + 2);
        g_issue(c, accG, 4, 0, false, 4); wg_wait<1>(); arrive_both(c, B_GEMPTY + 3);
        g_issue(c, accG, 0, 1, false, 5); wg_wait<1>(); arrive_both(c, B_GEMPTY + 4);
        int gs = 1, gph = 1;
        const int n0 = half ? 8 - NH0 : NH0, nt = 13 + n0;
#pragma unroll 1
        for (int t = 6; t < nt - TAIL_K; t++) {
            g_issue(c, accG, gs, gph, false, t, t == n0 + 9);
            wg_wait<1>();
            if (t + 4 < nt) arrive_both(c, B_GEMPTY + (gs == 0 ? 4 : gs - 1));
            if (++gs == 5) { gs = 0; gph ^= 1; }
        }
        const int R = (lane & 7) + (lane & 8), hi = lane >> 4;
        const int orow = tile * 64 + c.w * 16;
        auto stage_box = [&](int bx, uint32_t dst) {
#pragma unroll
            for (int p = 0; p < 2; p++) {
                const int G = 4 * bx + 2 * p;
                stsm4(dst + R * 64 + ((((G & 3) + hi) ^ ((R >> 1) & 3)) << 4),
                      pack2(accG[4 * G], accG[4 * G + 1]), pack2(accG[4 * G + 2], accG[4 * G + 3]),
                      pack2(accG[4 * G + 4], accG[4 * G + 5]), pack2(accG[4 * G + 6], accG[4 * G + 7]));
            }
        };
        auto out_col = [&](int bx) { return 160 * jj + ((G_ALIGN && (jj & 1)) ? (bx < 4 ? 32 * bx + 32 : 0) : 32 * bx); };
        if (c.w == 0) TRACE(18 + c.par);
        wg_wait<0>();
        {
            const uint32_t stg = sb + c.par * 4096 + c.w * 1024;
#pragma unroll
            for (int bx = 0; bx < 5; bx++) stage_box(bx, stg + (bx >> 1) * G_STAGE + (bx & 1) * 8192);
            asm volatile("fence.proxy.async.shared::cta;" ::: "memory");
            __syncwarp();
            if (elect_one()) {
#pragma unroll
                for (int bx = 0; bx < 5; bx++) tma3_red(&maps.o32, stg + (bx >> 1) * G_STAGE + (bx & 1) * 8192, out_col(bx), orow, c.par);
                asm volatile("cp.async.bulk.commit_group;" ::: "memory");
                asm volatile("cp.async.bulk.wait_group.read 0;" ::: "memory");
            }
        }
        if (c.w == 0) { TRACE(20 + c.par); TRACEG(60 + c.par); }
    }
}

namespace {
typedef CUresult (*EncodeFn)(CUtensorMap*, CUtensorMapDataType, cuuint32_t, void*, const cuuint64_t*, const cuuint64_t*, const cuuint32_t*,
                             const cuuint32_t*, CUtensorMapInterleave, CUtensorMapSwizzle, CUtensorMapL2promotion, CUtensorMapFloatOOBfill);

bool encode(EncodeFn fn, CUtensorMap* m, const void* ptr, int rank, const cuuint64_t* dims, const cuuint64_t* strides, const cuuint32_t* box,
            CUtensorMapSwizzle sw) {
    const cuuint32_t es[5] = {1, 1, 1, 1, 1};
    return fn(m, CU_TENSOR_MAP_DATA_TYPE_BFLOAT16, rank, const_cast<void*>(ptr), dims, strides, box, es, CU_TENSOR_MAP_INTERLEAVE_NONE, sw,
              CU_TENSOR_MAP_L2_PROMOTION_L2_128B, CU_TENSOR_MAP_FLOAT_OOB_FILL_NONE) == CUDA_SUCCESS;
}
}

extern "C" void kernel_launch(void* const* d_in, const int* in_sizes, int n_in, void* d_out, int out_size) {
    (void)in_sizes; (void)n_in; (void)out_size;
    const __nv_bfloat16* x = (const __nv_bfloat16*)d_in[0];
    const __nv_bfloat16* wqkv = (const __nv_bfloat16*)d_in[1];
    const __nv_bfloat16* wo = (const __nv_bfloat16*)d_in[2];
    const __nv_bfloat16* w1 = (const __nv_bfloat16*)d_in[4];
    const __nv_bfloat16* w3 = (const __nv_bfloat16*)d_in[5];
    const __nv_bfloat16* w2 = (const __nv_bfloat16*)d_in[6];

    static EncodeFn fn = nullptr;
    if (!fn) {
        void* p = nullptr;
        cudaDriverEntryPointQueryResult st;
        cudaGetDriverEntryPoint("cuTensorMapEncodeTiled", &p, cudaEnableDefault, &st);
        fn = (EncodeFn)p;
        cudaFuncSetAttribute(fused_block_kernel, cudaFuncAttributeMaxDynamicSharedMemorySize, SM_TOTAL);
    }
    Maps maps;
    {
        const cuuint64_t d[3] = {640, 1024, 2}, s[2] = {2560, 1280};
        const cuuint32_t b[3] = {64, 64, 2};
        encode(fn, &maps.x, x, 3, d, s, b, CU_TENSOR_MAP_SWIZZLE_128B);
    }
    {
        const cuuint64_t d[3] = {640, 640, 3}, s[2] = {3840, 1280};
        const cuuint32_t b[3] = {64, 16, 3}, br[3] = {16, 16, 3};
        encode(fn, &maps.wq, wqkv, 3, d, s, b, CU_TENSOR_MAP_SWIZZLE_128B);
        encode(fn, &maps.wqr, wqkv, 3, d, s, br, CU_TENSOR_MAP_SWIZZLE_32B);
    }
    {
        const cuuint64_t d[2] = {1536, 640}, s[1] = {3072};
        const cuuint32_t b[2] = {64, 64};
        encode(fn, &maps.w1, w1, 2, d, s, b, CU_TENSOR_MAP_SWIZZLE_128B);
        encode(fn, &maps.w3, w3, 2, d, s, b, CU_TENSOR_MAP_SWIZZLE_128B);
    }
    {
        const cuuint64_t d[2] = {1920, 640}, s[1] = {3840};
        const cuuint32_t b[2] = {256, 64};
        encode(fn, &maps.wqc, wqkv, 2, d, s, b, CU_TENSOR_MAP_SWIZZLE_NONE);
    }
    {
        const cuuint64_t d[2] = {1536, 640}, s[1] = {3072};
        const cuuint32_t b[2] = {256, 64};
        encode(fn, &maps.w1c, w1, 2, d, s, b, CU_TENSOR_MAP_SWIZZLE_NONE);
        encode(fn, &maps.w3c, w3, 2, d, s, b, CU_TENSOR_MAP_SWIZZLE_NONE);
    }
    {
        const cuuint64_t do5[5] = {640, 2, 80, 4, 2}, d25[5] = {640, 2, 192, 4, 2}, s5[4] = {1280, 10240, 2560, 128};
        const cuuint32_t b5[5] = {64, 2, 4, 4, 2}, b4[4] = {32, 2, 4, 4};
        encode(fn, &maps.wo2, wo, 5, do5, s5, b5, CU_TENSOR_MAP_SWIZZLE_128B);
        encode(fn, &maps.w22, w2, 5, d25, s5, b5, CU_TENSOR_MAP_SWIZZLE_128B);
        encode(fn, &maps.wo1, wo, 4, do5, s5, b4, CU_TENSOR_MAP_SWIZZLE_128B);
        encode(fn, &maps.w21, w2, 4, d25, s5, b4, CU_TENSOR_MAP_SWIZZLE_128B);
    }
    {
        const cuuint64_t d[3] = {640, 1024, 2}, s[2] = {2560, 1280};
        const cuuint32_t b64[3] = {64, 16, 1}, b32[3] = {32, 16, 1};
        encode(fn, &maps.o64, d_out, 3, d, s, b64, CU_TENSOR_MAP_SWIZZLE_128B);
        encode(fn, &maps.o32, d_out, 3, d, s, b32, CU_TENSOR_MAP_SWIZZLE_64B);
    }
    fused_block_kernel<<<132, 384, SM_TOTAL>>>(maps, x, wqkv, w1, w3, wo, w2, (__nv_bfloat16*)d_out);
}
```

```cpp
#include <cuda_runtime.h>
#include <cuda_bf16.h>
#include <cuda.h>
#include <stdint.h>

namespace {

constexpr int kS = 2048, kD = 640, kF = 1536;
constexpr int kActLd = kD + kF;

constexpr uint32_t SM_X = 0;
constexpr uint32_t SM_RING = 163840;
constexpr uint32_t SM_OWN = SM_RING + 3 * 16384;
constexpr uint32_t SM_MISC = 229376;
constexpr uint32_t SM_BAR = SM_MISC;
constexpr uint32_t SM_ST = SM_MISC + 448;
constexpr uint32_t SM_CSB0 = SM_ST + 1024;
constexpr uint32_t SM_CS = SM_CSB0 + 512;
constexpr uint32_t SM_TOTAL = 232448;
constexpr uint32_t G_STAGE = 40960;
static_assert(SM_CS + 1024 <= SM_TOTAL, "smem map");
__host__ __device__ constexpr uint32_t sm_csb(int f) { return f == 0 ? SM_CSB0 : SM_CS + (f - 1) * 512; }

constexpr int B_XFULL = 0;
constexpr int B_RFULL = 10;
constexpr int B_REMPTY = 14;
constexpr int B_GFULL = 18;
constexpr int B_GEMPTY = 23;
constexpr int B_CS = 28;
constexpr int B_ST = 29;
constexpr int B_CSB = 30;
constexpr int B_CSFREE = 33;
constexpr int B_HALOW = 34;
constexpr int B_HALOR = 35;
constexpr int B_WDONE = 37;
constexpr int B_FLAG = 41;
constexpr int B_INIT = 49;
constexpr int B_H1OUT = 50;
constexpr int B_COUNT = 51;
__host__ __device__ constexpr uint32_t bar_count(int i) {
    return ((i >= B_REMPTY && i < B_GFULL) || (i >= B_GEMPTY && i < B_CS)) ? 16
         : (i == B_CSFREE) ? 8
         : (i == B_HALOW) ? 2
         : (i == B_HALOR || i == B_HALOR + 1) ? 5
         : (i == B_WDONE + 1) ? 9
         : (i >= B_WDONE && i < B_FLAG) ? 8 : 1;
}

#define INIT_MODE 1
#define INIT_GAP 300
#define F2_EXPOSED 1
#define SLOT_ROT 0
#define RF_ALIGN 1
#define POLL_GAP 350
#define G_ALIGN 1
#define G_SPLIT 46
#define POLL_FENCE 1
#define G_AUX 1
#define G_AUX_GAP 100
#define WAIT_FAST 1
#define AOFF_KEEP 1
#define STAGGER 0
#define KEEP_ADDR 1
#define X_EARLY 1
#define CS_WAIT 8
#define GATHER_GAP 350
#define JOBA_REV 1
#define TAIL_K 0
#define START_PF 1
#define FAST_START 1
#define G_MAP 1
#define H1_SPREAD 0
#define FENCE_LATE 2
#define EDGE_AFTER 0
#define TAIL64 2
#define CS_PRE_ALL 0
#define G_EARLY 47
#define NH0 4

constexpr int PF_DIST = 6;
#define SILU_TANH 1

__device__ __align__(1024) uint8_t g_act[16 * 34 * 16384];
__device__ __align__(128) unsigned g_csA[4 * 3 * kD];
__device__ __align__(128) unsigned g_csB[2 * 2 * kF];
__device__ __align__(128) unsigned g_stats[kS * 2];
__device__ __align__(128) uint4 g_halo[16 * 8 * 2 * 4 * 5 * 32];
__device__ __align__(128) unsigned g_cntO[16 * 32];
__device__ __align__(128) unsigned g_cntH[16 * 32];
__device__ __align__(128) unsigned g_flagHalo[16 * 8 * 32];
__device__ __align__(128) unsigned g_flagH[2 * 16 * 8 * 32];
#define TP(p) do { } while (0)
#define TRACEFG(slot) do { } while (0)
#define TRACEP(slot) do { } while (0)
#define TRACEF(slot) do { } while (0)
#define TRACE(slot) do { } while (0)
#define TRACEG(slot) do { } while (0)

struct Maps {
    CUtensorMap x, wq, wqr, w1, w3, wo2, wo1, w22, w21, o64, o32, w1c, w3c, wqc;
};

__device__ __forceinline__ long long gtime() { long long t; asm volatile("mov.u64 %0, %%globaltimer;" : "=l"(t)); return t; }
__device__ __forceinline__ uint32_t smem_u32(const void* p) { return (uint32_t)__cvta_generic_to_shared(p); }
__device__ __forceinline__ uint32_t launder(uint32_t x) { uint32_t y; asm volatile("mov.u32 %0, %1;" : "=r"(y) : "r"(x)); return y; }
template <class T> __device__ __forceinline__ T* launder_ptr(T* p) { T* q; asm volatile("mov.u64 %0, %1;" : "=l"(q) : "l"(p)); return q; }
__device__ __forceinline__ void keep_alive(const void* p, int lane) {
    asm volatile("{\n.reg .pred q;\nsetp.eq.s32 q, %1, 77;\n@q st.global.u32 [%0], %1;\n}" ::"l"(p), "r"(lane));
}
__device__ __forceinline__ bool elect_one() {
    uint32_t p;
    asm volatile("{\n.reg .pred P;\nelect.sync _|P, 0xffffffff;\nselp.u32 %0,1,0,P;\n}" : "=r"(p));
    return p;
}
__device__ __forceinline__ void mbar_init(uint32_t bar, uint32_t cnt) { asm volatile("mbarrier.init.shared::cta.b64 [%0], %1;" ::"r"(bar), "r"(cnt)); }
__device__ __forceinline__ void mbar_expect_tx(uint32_t bar, uint32_t bytes) {
    asm volatile("mbarrier.arrive.expect_tx.shared::cta.b64 _, [%0], %1;" ::"r"(bar), "r"(bytes) : "memory");
}
__device__ __forceinline__ void mbar_arrive(uint32_t bar) { asm volatile("mbarrier.arrive.shared::cta.b64 _, [%0];" ::"r"(bar) : "memory"); }
__device__ __forceinline__ void mbar_arrive_cluster(uint32_t bar_cluster_addr) {
    asm volatile("mbarrier.arrive.shared::cluster.b64 _, [%0];" ::"r"(bar_cluster_addr) : "memory");
}
__device__ __forceinline__ uint32_t mapa(uint32_t addr, uint32_t cta) {
    uint32_t r; asm("mapa.shared::cluster.u32 %0, %1, %2;" : "=r"(r) : "r"(addr), "r"(cta)); return r;
}
__device__ __forceinline__ bool mbar_try(uint32_t bar, uint32_t parity) {
    uint32_t ok;
    asm volatile("{\n.reg .pred p;\nmbarrier.try_wait.parity.shared::cta.b64 p, [%1], %2;\nselp.u32 %0,1,0,p;\n}"
                 : "=r"(ok) : "r"(bar), "r"(parity) : "memory");
    return ok;
}
__device__ __forceinline__ void mbar_wait(uint32_t bar, uint32_t parity) {
    if (mbar_try(bar, parity)) return;
    int it = 0;
#pragma unroll 1
    while (!mbar_try(bar, parity)) { if (++it > (1 << 17)) break; }
}
__device__ __forceinline__ void tma2(uint32_t dst, const CUtensorMap* m, int c0, int c1, uint32_t bar) {
    asm volatile("cp.async.bulk.tensor.2d.shared::cluster.global.mbarrier::complete_tx::bytes [%0], [%1, {%3, %4}], [%2];"
                 ::"r"(dst), "l"(m), "r"(bar), "r"(c0), "r"(c1) : "memory");
}
__device__ __forceinline__ void tma3(uint32_t dst, const CUtensorMap* m, int c0, int c1, int c2, uint32_t bar) {
    asm volatile("cp.async.bulk.tensor.3d.shared::cluster.global.mbarrier::complete_tx::bytes [%0], [%1, {%3, %4, %5}], [%2];"
                 ::"r"(dst), "l"(m), "r"(bar), "r"(c0), "r"(c1), "r"(c2) : "memory");
}
__device__ __forceinline__ void tma2_mc(uint32_t dst, const CUtensorMap* m, int c0, int c1, uint32_t bar) {
    asm volatile("cp.async.bulk.tensor.2d.shared::cluster.global.mbarrier::complete_tx::bytes.multicast::cluster [%0], [%1, {%3, %4}], [%2], %5;"
                 ::"r"(dst), "l"(m), "r"(bar), "r"(c0), "r"(c1), "h"((uint16_t)3) : "memory");
}
__device__ __forceinline__ void tma3_mc(uint32_t dst, const CUtensorMap* m, int c0, int c1, int c2, uint32_t bar) {
    asm volatile("cp.async.bulk.tensor.3d.shared::cluster.global.mbarrier::complete_tx::bytes.multicast::cluster [%0], [%1, {%3, %4, %5}], [%2], %6;"
                 ::"r"(dst), "l"(m), "r"(bar), "r"(c0), "r"(c1), "r"(c2), "h"((uint16_t)3) : "memory");
}
__device__ __forceinline__ void tma4_mc(uint32_t dst, const CUtensorMap* m, int c0, int c2, uint32_t bar) {
    asm volatile("cp.async.bulk.tensor.4d.shared::cluster.global.mbarrier::complete_tx::bytes.multicast::cluster [%0], [%1, {%3, %5, %4, %5}], [%2], %6;"
                 ::"r"(dst), "l"(m), "r"(bar), "r"(c0), "r"(c2), "r"(0), "h"((uint16_t)3) : "memory");
}
__device__ __forceinline__ void tma5_mc(uint32_t dst, const CUtensorMap* m, int c0, int c2, uint32_t bar) {
    asm volatile("cp.async.bulk.tensor.5d.shared::cluster.global.mbarrier::complete_tx::bytes.multicast::cluster [%0], [%1, {%3, %5, %4, %5, %5}], [%2], %6;"
                 ::"r"(dst), "l"(m), "r"(bar), "r"(c0), "r"(c2), "r"(0), "h"((uint16_t)3) : "memory");
}
__device__ __forceinline__ void bulk_g2s(uint32_t dst, const void* src, uint32_t bytes, uint32_t bar) {
    asm volatile("cp.async.bulk.shared::cluster.global.mbarrier::complete_tx::bytes [%0], [%1], %2, [%3];"
                 ::"r"(dst), "l"(src), "r"(bytes), "r"(bar) : "memory");
}
__device__ __forceinline__ uint4 lds128(uint32_t a) {
    uint4 v; asm volatile("ld.shared.v4.u32 {%0,%1,%2,%3}, [%4];" : "=r"(v.x), "=r"(v.y), "=r"(v.z), "=r"(v.w) : "r"(a) : "memory"); return v;
}
__device__ __forceinline__ void sts128(uint32_t a, uint4 v) {
    asm volatile("st.shared.v4.u32 [%0], {%1,%2,%3,%4};" ::"r"(a), "r"(v.x), "r"(v.y), "r"(v.z), "r"(v.w) : "memory");
}
__device__ __forceinline__ void prefetch_map(const CUtensorMap* m) { asm volatile("prefetch.tensormap [%0];" ::"l"(m) : "memory"); }
__device__ __forceinline__ void prefetch_l2(const void* p, uint32_t bytes) {
    asm volatile("cp.async.bulk.prefetch.L2.global [%0], %1;" ::"l"(p), "r"(bytes) : "memory");
}
__device__ __forceinline__ void wg_fence() { asm volatile("wgmma.fence.sync.aligned;" ::: "memory"); }
__device__ __forceinline__ void wg_commit() { asm volatile("wgmma.commit_group.sync.aligned;" ::: "memory"); }
template <int N> __device__ __forceinline__ void wg_wait() { asm volatile("wgmma.wait_group.sync.aligned %0;" ::"n"(N) : "memory"); }
__device__ __forceinline__ unsigned ld_acquire(const unsigned* p) {
    unsigned v; asm volatile("ld.acquire.gpu.global.u32 %0, [%1];" : "=r"(v) : "l"(p) : "memory"); return v;
}
__device__ __forceinline__ void fence_gpu() { asm volatile("fence.acq_rel.gpu;" ::: "memory"); }
__device__ __forceinline__ void fence_async_global() { asm volatile("fence.proxy.async.global;" ::: "memory"); }
__device__ __forceinline__ void red_add(unsigned* p, unsigned v) { asm volatile("red.relaxed.gpu.global.add.u32 [%0], %1;" ::"l"(p), "r"(v) : "memory"); }
__device__ __forceinline__ void st_relaxed(unsigned* p, unsigned v) { asm volatile("st.relaxed.gpu.global.u32 [%0], %1;" ::"l"(p), "r"(v) : "memory"); }
__device__ __forceinline__ unsigned ld_relaxed(const unsigned* p) {
    unsigned v; asm volatile("ld.relaxed.gpu.global.u32 %0, [%1];" : "=r"(v) : "l"(p) : "memory"); return v;
}
__device__ __forceinline__ unsigned tagged(unsigned tag, float v) { return ((__float_as_uint(v) + 8u) & ~15u) | (tag & 15u); }
__device__ __forceinline__ bool tag_ok(const uint4& v, unsigned tag) { return (((v.x ^ tag) | (v.y ^ tag) | (v.z ^ tag) | (v.w ^ tag)) & 15u) == 0; }
__device__ __forceinline__ float tag_val(unsigned v) { return __uint_as_float(v & ~15u); }
__device__ __forceinline__ void st_tag(unsigned* p, unsigned a) { asm volatile("st.relaxed.gpu.global.u32 [%0], %1;" ::"l"(p), "r"(a) : "memory"); }
__device__ __forceinline__ void st_tag2(unsigned* p, unsigned a, unsigned b) {
    asm volatile("st.relaxed.gpu.global.v2.u32 [%0], {%1, %2};" ::"l"(p), "r"(a), "r"(b) : "memory");
}
__device__ __forceinline__ void st_tag4(unsigned* p, unsigned a, unsigned b, unsigned c, unsigned d) {
    asm volatile("st.relaxed.gpu.global.v4.u32 [%0], {%1, %2, %3, %4};" ::"l"(p), "r"(a), "r"(b), "r"(c), "r"(d) : "memory");
}
__device__ __forceinline__ uint4 ld_tag4(const unsigned* p) {
    uint4 v; asm volatile("ld.relaxed.gpu.global.v4.u32 {%0,%1,%2,%3}, [%4];" : "=r"(v.x), "=r"(v.y), "=r"(v.z), "=r"(v.w) : "l"(p) : "memory"); return v;
}
__device__ __forceinline__ void poll_ge(const unsigned* p, unsigned target) {
    int it = 0;
#pragma unroll 1
    while ((int)(ld_acquire(p) - target) < 0) { if (++it > (1 << 16)) break; }
}
__device__ __forceinline__ void spin(int cycles) { const long long t0 = clock64(); while (clock64() - t0 < cycles) { } }
#define PROXY_FENCE() fence_async_global()
__device__ __forceinline__ void gather2(const unsigned* p0, const unsigned* p1, unsigned tag, uint4& r0, uint4& r1) {
    uint4 a0 = ld_tag4(p0), a1 = ld_tag4(p1);
    spin(GATHER_GAP);
    uint4 b0 = ld_tag4(p0), b1 = ld_tag4(p1);
    spin(GATHER_GAP);
    uint4 c0 = ld_tag4(p0), c1 = ld_tag4(p1);
#pragma unroll 1
    for (int it = 0; it < (1 << 14); it++) {
        if (__all_sync(0xffffffffu, tag_ok(a0, tag) && tag_ok(a1, tag))) { r0 = a0; r1 = a1; return; }
        a0 = ld_tag4(p0); a1 = ld_tag4(p1);
        if (__all_sync(0xffffffffu, tag_ok(b0, tag) && tag_ok(b1, tag))) { r0 = b0; r1 = b1; return; }
        b0 = ld_tag4(p0); b1 = ld_tag4(p1);
        if (__all_sync(0xffffffffu, tag_ok(c0, tag) && tag_ok(c1, tag))) { r0 = c0; r1 = c1; return; }
        c0 = ld_tag4(p0); c1 = ld_tag4(p1);
    }
    r0 = a0; r1 = a1;
}
__device__ __forceinline__ void poll_multi(const unsigned* p, unsigned target, uint32_t bar, bool active) {
    bool done = !active;
    unsigned v0 = 0, v1 = 0, v2 = 0;
    if (!done) v0 = ld_relaxed(p);
    spin(POLL_GAP);
    if (!done) v1 = ld_relaxed(p);
    spin(POLL_GAP);
    if (!done) v2 = ld_relaxed(p);
#pragma unroll 1
    for (int it = 0; it < (1 << 15); it++) {
        if (!done && (int)(v0 - target) >= 0) { PROXY_FENCE(); mbar_arrive(bar); done = true; }
        if (__all_sync(0xffffffffu, done)) return;
        if (!done) v0 = ld_relaxed(p);
        if (!done && (int)(v1 - target) >= 0) { PROXY_FENCE(); mbar_arrive(bar); done = true; }
        if (__all_sync(0xffffffffu, done)) return;
        if (!done) v1 = ld_relaxed(p);
        if (!done && (int)(v2 - target) >= 0) { PROXY_FENCE(); mbar_arrive(bar); done = true; }
        if (__all_sync(0xffffffffu, done)) return;
        if (!done) v2 = ld_relaxed(p);
    }
    if (!done) mbar_arrive(bar);
}
template <int ID, int N> __device__ __forceinline__ void bar_sync() { asm volatile("bar.sync %0, %1;" ::"n"(ID), "n"(N) : "memory"); }
__device__ __forceinline__ float ex2(float x) { float y; asm("ex2.approx.ftz.f32 %0, %1;" : "=f"(y) : "f"(x)); return y; }
__device__ __forceinline__ float rcp(float x) { float y; asm("rcp.approx.ftz.f32 %0, %1;" : "=f"(y) : "f"(x)); return y; }
__device__ __forceinline__ float tanh_fast(float x) { float y; asm("tanh.approx.f32 %0, %1;" : "=f"(y) : "f"(x)); return y; }
__device__ __forceinline__ uint32_t badd2(uint32_t a, uint32_t b) { uint32_t d; asm("add.rn.bf16x2 %0, %1, %2;" : "=r"(d) : "r"(a), "r"(b)); return d; }
__device__ __forceinline__ uint32_t lds32(uint32_t a) { uint32_t v; asm volatile("ld.shared.u32 %0, [%1];" : "=r"(v) : "r"(a) : "memory"); return v; }
__device__ __forceinline__ uint32_t pack2(float lo, float hi) {
    uint32_t r; asm("cvt.rn.bf16x2.f32 %0, %1, %2;" : "=r"(r) : "f"(hi), "f"(lo)); return r;
}
__device__ __forceinline__ float bf_lo(uint32_t v) { return __uint_as_float(v << 16); }
__device__ __forceinline__ float bf_hi(uint32_t v) { return __uint_as_float(v & 0xffff0000u); }
__device__ __forceinline__ float2 lds64_const(uint32_t a) { float2 v; asm("ld.shared.v2.f32 {%0,%1}, [%2];" : "=f"(v.x), "=f"(v.y) : "r"(a)); return v; }
__device__ __forceinline__ float2 lds64(uint32_t a) { float2 v; asm volatile("ld.shared.v2.f32 {%0,%1}, [%2];" : "=f"(v.x), "=f"(v.y) : "r"(a)); return v; }
__device__ __forceinline__ void mma16(float (&c)[4], uint32_t a0, uint32_t a1, uint32_t a2, uint32_t a3, uint32_t b0, uint32_t b1) {
    asm("mma.sync.aligned.m16n8k16.row.col.f32.bf16.bf16.f32 {%0,%1,%2,%3}, {%4,%5,%6,%7}, {%8,%9}, {%0,%1,%2,%3};"
        : "+f"(c[0]), "+f"(c[1]), "+f"(c[2]), "+f"(c[3]) : "r"(a0), "r"(a1), "r"(a2), "r"(a3), "r"(b0), "r"(b1));
}
__device__ __forceinline__ void mma8(float (&c)[4], uint32_t a0, uint32_t a1, uint32_t b0) {
    asm("mma.sync.aligned.m16n8k8.row.col.f32.bf16.bf16.f32 {%0,%1,%2,%3}, {%4,%5}, {%6}, {%0,%1,%2,%3};"
        : "+f"(c[0]), "+f"(c[1]), "+f"(c[2]), "+f"(c[3]) : "r"(a0), "r"(a1), "r"(b0));
}
__device__ __forceinline__ void mma16v(float (&d)[4], uint32_t a0, uint32_t a1, uint32_t a2, uint32_t a3, uint32_t b0, uint32_t b1,
                                       float c0, float c1, float c2, float c3) {
    asm volatile("mma.sync.aligned.m16n8k16.row.col.f32.bf16.bf16.f32 {%0,%1,%2,%3}, {%4,%5,%6,%7}, {%8,%9}, {%10,%11,%12,%13};"
        : "=f"(d[0]), "=f"(d[1]), "=f"(d[2]), "=f"(d[3]) : "r"(a0), "r"(a1), "r"(a2), "r"(a3), "r"(b0), "r"(b1), "f"(c0), "f"(c1), "f"(c2), "f"(c3));
}
__device__ __forceinline__ void mma8v(float (&c)[4], uint32_t a0, uint32_t a1, uint32_t b0) {
    asm volatile("mma.sync.aligned.m16n8k8.row.col.f32.bf16.bf16.f32 {%0,%1,%2,%3}, {%4,%5}, {%6}, {%0,%1,%2,%3};"
        : "+f"(c[0]), "+f"(c[1]), "+f"(c[2]), "+f"(c[3]) : "r"(a0), "r"(a1), "r"(b0));
}
__device__ __forceinline__ uint32_t pack2v(float lo, float hi) {
    uint32_t r; asm volatile("cvt.rn.bf16x2.f32 %0, %1, %2;" : "=r"(r) : "f"(hi), "f"(lo)); return r;
}
__device__ __forceinline__ uint32_t andv(uint32_t a, uint32_t b) {
    uint32_t r; asm volatile("and.b32 %0, %1, %2;" : "=r"(r) : "r"(a), "r"(b)); return r;
}
__device__ __forceinline__ uint32_t movv(uint32_t a) {
    uint32_t r; asm volatile("mov.b32 %0, %1;" : "=r"(r) : "r"(a)); return r;
}
__device__ __forceinline__ uint32_t movm(uint32_t a) {
    uint32_t d; asm volatile("movmatrix.sync.aligned.m8n8.trans.b16 %0, %1;" : "=r"(d) : "r"(a)); return d;
}

__device__ __forceinline__ void wgmma_n48(float (&d)[24], uint32_t alo, uint32_t ahi, uint32_t blo, uint32_t bhi, int sd) {
    asm volatile("{\n.reg .pred p;\n.reg .b64 da, db;\nsetp.ne.b32 p, %28, 0;\nmov.b64 da, {%24,%25};\nmov.b64 db, {%26,%27};\n"
        "wgmma.mma_async.sync.aligned.m64n48k16.f32.bf16.bf16 {"
        "%0,%1,%2,%3,%4,%5,%6,%7,%8,%9,%10,%11,%12,%13,%14,%15,"
        "%16,%17,%18,%19,%20,%21,%22,%23"
        "}, da, db, p, 1, 1, 0, 1;\n}\n"
        : "+f"(d[0]), "+f"(d[1]), "+f"(d[2]), "+f"(d[3]), "+f"(d[4]), "+f"(d[5]), "+f"(d[6]), "+f"(d[7]),
          "+f"(d[8]), "+f"(d[9]), "+f"(d[10]), "+f"(d[11]), "+f"(d[12]), "+f"(d[13]), "+f"(d[14]), "+f"(d[15]),
          "+f"(d[16]), "+f"(d[17]), "+f"(d[18]), "+f"(d[19]), "+f"(d[20]), "+f"(d[21]), "+f"(d[22]), "+f"(d[23])
        : "r"(alo), "r"(ahi), "r"(blo), "r"(bhi), "r"(sd));
}
__device__ __forceinline__ void wgmma_n128(float (&d)[64], uint32_t alo, uint32_t ahi, uint32_t blo, uint32_t bhi, int sd) {
    asm volatile("{\n.reg .pred p;\n.reg .b64 da, db;\nsetp.ne.b32 p, %68, 0;\nmov.b64 da, {%64,%65};\nmov.b64 db, {%66,%67};\n"
        "wgmma.mma_async.sync.aligned.m64n128k16.f32.bf16.bf16 {"
        "%0,%1,%2,%3,%4,%5,%6,%7,%8,%9,%10,%11,%12,%13,%14,%15,"
        "%16,%17,%18,%19,%20,%21,%22,%23,%24,%25,%26,%27,%28,%29,%30,%31,"
        "%32,%33,%34,%35,%36,%37,%38,%39,%40,%41,%42,%43,%44,%45,%46,%47,"
        "%48,%49,%50,%51,%52,%53,%54,%55,%56,%57,%58,%59,%60,%61,%62,%63"
        "}, da, db, p, 1, 1, 0, 1;\n}\n"
        : "+f"(d[0]), "+f"(d[1]), "+f"(d[2]), "+f"(d[3]), "+f"(d[4]), "+f"(d[5]), "+f"(d[6]), "+f"(d[7]),
          "+f"(d[8]), "+f"(d[9]), "+f"(d[10]), "+f"(d[11]), "+f"(d[12]), "+f"(d[13]), "+f"(d[14]), "+f"(d[15]),
          "+f"(d[16]), "+f"(d[17]), "+f"(d[18]), "+f"(d[19]), "+f"(d[20]), "+f"(d[21]), "+f"(d[22]), "+f"(d[23]),
          "+f"(d[24]), "+f"(d[25]), "+f"(d[26]), "+f"(d[27]), "+f"(d[28]), "+f"(d[29]), "+f"(d[30]), "+f"(d[31]),
          "+f"(d[32]), "+f"(d[33]), "+f"(d[34]), "+f"(d[35]), "+f"(d[36]), "+f"(d[37]), "+f"(d[38]), "+f"(d[39]),
          "+f"(d[40]), "+f"(d[41]), "+f"(d[42]), "+f"(d[43]), "+f"(d[44]), "+f"(d[45]), "+f"(d[46]), "+f"(d[47]),
          "+f"(d[48]), "+f"(d[49]), "+f"(d[50]), "+f"(d[51]), "+f"(d[52]), "+f"(d[53]), "+f"(d[54]), "+f"(d[55]),
          "+f"(d[56]), "+f"(d[57]), "+f"(d[58]), "+f"(d[59]), "+f"(d[60]), "+f"(d[61]), "+f"(d[62]), "+f"(d[63])
        : "r"(alo), "r"(ahi), "r"(blo), "r"(bhi), "r"(sd));
}
__device__ __forceinline__ void wgmma_n160(float (&d)[80], uint32_t alo, uint32_t ahi, uint32_t blo, uint32_t bhi, int sd) {
    asm volatile("{\n.reg .pred p;\n.reg .b64 da, db;\nsetp.ne.b32 p, %84, 0;\nmov.b64 da, {%80,%81};\nmov.b64 db, {%82,%83};\n"
        "wgmma.mma_async.sync.aligned.m64n160k16.f32.bf16.bf16 {"
        "%0,%1,%2,%3,%4,%5,%6,%7,%8,%9,%10,%11,%12,%13,%14,%15,"
        "%16,%17,%18,%19,%20,%21,%22,%23,%24,%25,%26,%27,%28,%29,%30,%31,"
        "%32,%33,%34,%35,%36,%37,%38,%39,%40,%41,%42,%43,%44,%45,%46,%47,"
        "%48,%49,%50,%51,%52,%53,%54,%55,%56,%57,%58,%59,%60,%61,%62,%63,"
        "%64,%65,%66,%67,%68,%69,%70,%71,%72,%73,%74,%75,%76,%77,%78,%79"
        "}, da, db, p, 1, 1, 0, 1;\n}\n"
        : "+f"(d[0]), "+f"(d[1]), "+f"(d[2]), "+f"(d[3]), "+f"(d[4]), "+f"(d[5]), "+f"(d[6]), "+f"(d[7]),
          "+f"(d[8]), "+f"(d[9]), "+f"(d[10]), "+f"(d[11]), "+f"(d[12]), "+f"(d[13]), "+f"(d[14]), "+f"(d[15]),
          "+f"(d[16]), "+f"(d[17]), "+f"(d[18]), "+f"(d[19]), "+f"(d[20]), "+f"(d[21]), "+f"(d[22]), "+f"(d[23]),
          "+f"(d[24]), "+f"(d[25]), "+f"(d[26]), "+f"(d[27]), "+f"(d[28]), "+f"(d[29]), "+f"(d[30]), "+f"(d[31]),
          "+f"(d[32]), "+f"(d[33]), "+f"(d[34]), "+f"(d[35]), "+f"(d[36]), "+f"(d[37]), "+f"(d[38]), "+f"(d[39]),
          "+f"(d[40]), "+f"(d[41]), "+f"(d[42]), "+f"(d[43]), "+f"(d[44]), "+f"(d[45]), "+f"(d[46]), "+f"(d[47]),
          "+f"(d[48]), "+f"(d[49]), "+f"(d[50]), "+f"(d[51]), "+f"(d[52]), "+f"(d[53]), "+f"(d[54]), "+f"(d[55]),
          "+f"(d[56]), "+f"(d[57]), "+f"(d[58]), "+f"(d[59]), "+f"(d[60]), "+f"(d[61]), "+f"(d[62]), "+f"(d[63]),
          "+f"(d[64]), "+f"(d[65]), "+f"(d[66]), "+f"(d[67]), "+f"(d[68]), "+f"(d[69]), "+f"(d[70]), "+f"(d[71]),
          "+f"(d[72]), "+f"(d[73]), "+f"(d[74]), "+f"(d[75]), "+f"(d[76]), "+f"(d[77]), "+f"(d[78]), "+f"(d[79])
        : "r"(alo), "r"(ahi), "r"(blo), "r"(bhi), "r"(sd));
}
__device__ __forceinline__ void wgmma_n192(float (&d)[96], uint32_t alo, uint32_t ahi, uint32_t blo, uint32_t bhi, int sd) {
    asm volatile("{\n.reg .pred p;\n.reg .b64 da, db;\nsetp.ne.b32 p, %100, 0;\nmov.b64 da, {%96,%97};\nmov.b64 db, {%98,%99};\n"
        "wgmma.mma_async.sync.aligned.m64n192k16.f32.bf16.bf16 {"
        "%0,%1,%2,%3,%4,%5,%6,%7,%8,%9,%10,%11,%12,%13,%14,%15,"
        "%16,%17,%18,%19,%20,%21,%22,%23,%24,%25,%26,%27,%28,%29,%30,%31,"
        "%32,%33,%34,%35,%36,%37,%38,%39,%40,%41,%42,%43,%44,%45,%46,%47,"
        "%48,%49,%50,%51,%52,%53,%54,%55,%56,%57,%58,%59,%60,%61,%62,%63,"
        "%64,%65,%66,%67,%68,%69,%70,%71,%72,%73,%74,%75,%76,%77,%78,%79,"
        "%80,%81,%82,%83,%84,%85,%86,%87,%88,%89,%90,%91,%92,%93,%94,%95"
        "}, da, db, p, 1, 1, 0, 1;\n}\n"
        : "+f"(d[0]), "+f"(d[1]), "+f"(d[2]), "+f"(d[3]), "+f"(d[4]), "+f"(d[5]), "+f"(d[6]), "+f"(d[7]),
          "+f"(d[8]), "+f"(d[9]), "+f"(d[10]), "+f"(d[11]), "+f"(d[12]), "+f"(d[13]), "+f"(d[14]), "+f"(d[15]),
          "+f"(d[16]), "+f"(d[17]), "+f"(d[18]), "+f"(d[19]), "+f"(d[20]), "+f"(d[21]), "+f"(d[22]), "+f"(d[23]),
          "+f"(d[24]), "+f"(d[25]), "+f"(d[26]), "+f"(d[27]), "+f"(d[28]), "+f"(d[29]), "+f"(d[30]), "+f"(d[31]),
          "+f"(d[32]), "+f"(d[33]), "+f"(d[34]), "+f"(d[35]), "+f"(d[36]), "+f"(d[37]), "+f"(d[38]), "+f"(d[39]),
          "+f"(d[40]), "+f"(d[41]), "+f"(d[42]), "+f"(d[43]), "+f"(d[44]), "+f"(d[45]), "+f"(d[46]), "+f"(d[47]),
          "+f"(d[48]), "+f"(d[49]), "+f"(d[50]), "+f"(d[51]), "+f"(d[52]), "+f"(d[53]), "+f"(d[54]), "+f"(d[55]),
          "+f"(d[56]), "+f"(d[57]), "+f"(d[58]), "+f"(d[59]), "+f"(d[60]), "+f"(d[61]), "+f"(d[62]), "+f"(d[63]),
          "+f"(d[64]), "+f"(d[65]), "+f"(d[66]), "+f"(d[67]), "+f"(d[68]), "+f"(d[69]), "+f"(d[70]), "+f"(d[71]),
          "+f"(d[72]), "+f"(d[73]), "+f"(d[74]), "+f"(d[75]), "+f"(d[76]), "+f"(d[77]), "+f"(d[78]), "+f"(d[79]),
          "+f"(d[80]), "+f"(d[81]), "+f"(d[82]), "+f"(d[83]), "+f"(d[84]), "+f"(d[85]), "+f"(d[86]), "+f"(d[87]),
          "+f"(d[88]), "+f"(d[89]), "+f"(d[90]), "+f"(d[91]), "+f"(d[92]), "+f"(d[93]), "+f"(d[94]), "+f"(d[95])
        : "r"(alo), "r"(ahi), "r"(blo), "r"(bhi), "r"(sd));
}
__device__ __forceinline__ void wgmma_n96(float (&d)[48], uint32_t alo, uint32_t ahi, uint32_t blo, uint32_t bhi, int sd) {
    asm volatile("{\n.reg .pred p;\n.reg .b64 da, db;\nsetp.ne.b32 p, %52, 0;\nmov.b64 da, {%48,%49};\nmov.b64 db, {%50,%51};\n"
        "wgmma.mma_async.sync.aligned.m64n96k16.f32.bf16.bf16 {"
        "%0,%1,%2,%3,%4,%5,%6,%7,%8,%9,%10,%11,%12,%13,%14,%15,"
        "%16,%17,%18,%19,%20,%21,%22,%23,%24,%25,%26,%27,%28,%29,%30,%31,"
        "%32,%33,%34,%35,%36,%37,%38,%39,%40,%41,%42,%43,%44,%45,%46,%47"
        "}, da, db, p, 1, 1, 0, 1;\n}\n"
        : "+f"(d[0]), "+f"(d[1]), "+f"(d[2]), "+f"(d[3]), "+f"(d[4]), "+f"(d[5]), "+f"(d[6]), "+f"(d[7]),
          "+f"(d[8]), "+f"(d[9]), "+f"(d[10]), "+f"(d[11]), "+f"(d[12]), "+f"(d[13]), "+f"(d[14]), "+f"(d[15]),
          "+f"(d[16]), "+f"(d[17]), "+f"(d[18]), "+f"(d[19]), "+f"(d[20]), "+f"(d[21]), "+f"(d[22]), "+f"(d[23]),
          "+f"(d[24]), "+f"(d[25]), "+f"(d[26]), "+f"(d[27]), "+f"(d[28]), "+f"(d[29]), "+f"(d[30]), "+f"(d[31]),
          "+f"(d[32]), "+f"(d[33]), "+f"(d[34]), "+f"(d[35]), "+f"(d[36]), "+f"(d[37]), "+f"(d[38]), "+f"(d[39]),
          "+f"(d[40]), "+f"(d[41]), "+f"(d[42]), "+f"(d[43]), "+f"(d[44]), "+f"(d[45]), "+f"(d[46]), "+f"(d[47])
        : "r"(alo), "r"(ahi), "r"(blo), "r"(bhi), "r"(sd));
}
__device__ __forceinline__ void wgmma_n64(float (&d)[32], uint32_t alo, uint32_t ahi, uint32_t blo, uint32_t bhi, int sd) {
    asm volatile("{\n.reg .pred p;\n.reg .b64 da, db;\nsetp.ne.b32 p, %36, 0;\nmov.b64 da, {%32,%33};\nmov.b64 db, {%34,%35};\n"
        "wgmma.mma_async.sync.aligned.m64n64k16.f32.bf16.bf16 {"
        "%0,%1,%2,%3,%4,%5,%6,%7,%8,%9,%10,%11,%12,%13,%14,%15,"
        "%16,%17,%18,%19,%20,%21,%22,%23,%24,%25,%26,%27,%28,%29,%30,%31"
        "}, da, db, p, 1, 1, 0, 1;\n}\n"
        : "+f"(d[0]), "+f"(d[1]), "+f"(d[2]), "+f"(d[3]), "+f"(d[4]), "+f"(d[5]), "+f"(d[6]), "+f"(d[7]),
          "+f"(d[8]), "+f"(d[9]), "+f"(d[10]), "+f"(d[11]), "+f"(d[12]), "+f"(d[13]), "+f"(d[14]), "+f"(d[15]),
          "+f"(d[16]), "+f"(d[17]), "+f"(d[18]), "+f"(d[19]), "+f"(d[20]), "+f"(d[21]), "+f"(d[22]), "+f"(d[23]),
          "+f"(d[24]), "+f"(d[25]), "+f"(d[26]), "+f"(d[27]), "+f"(d[28]), "+f"(d[29]), "+f"(d[30]), "+f"(d[31])
        : "r"(alo), "r"(ahi), "r"(blo), "r"(bhi), "r"(sd));
}

constexpr uint32_t HI_128 = 0x40000040u;
constexpr uint32_t HI_64 = 0x80000020u;
constexpr uint32_t HI_32 = 0xC0000010u;
__device__ __forceinline__ constexpr uint32_t lbo(uint32_t bytes) { return (bytes >> 4) << 16; }

struct Ctx {
    uint32_t sb;
    uint32_t bar;
    uint32_t rbar;
    uint32_t a_lo;
    uint32_t b_lo;
    int lane, q, g, w, par;
    uint32_t aoff;
    float m0, m1, r0, r1;
    float ga0, ga1, gb0, gb1;
};

__device__ __forceinline__ void arrive_both(const Ctx& c, int bar_idx) {
    if (c.lane < 2) mbar_arrive_cluster(c.rbar + bar_idx * 8);
}
__device__ __forceinline__ void arrive_local(const Ctx& c, int bar_idx) {
    __syncwarp();
    if (c.lane == 0) mbar_arrive(c.bar + bar_idx * 8);
}

__device__ __forceinline__ void stsm4(uint32_t addr, uint32_t a, uint32_t b, uint32_t c, uint32_t d) {
    asm volatile("stmatrix.sync.aligned.m8n8.x4.shared.b16 [%0], {%1, %2, %3, %4};" ::"r"(addr), "r"(a), "r"(b), "r"(c), "r"(d) : "memory");
}
__device__ __forceinline__ void tma3_store(const CUtensorMap* m, uint32_t src, int c0, int c1, int c2) {
    asm volatile("cp.async.bulk.tensor.3d.global.shared::cta.tile.bulk_group [%0, {%2, %3, %4}], [%1];"
                 ::"l"(m), "r"(src), "r"(c0), "r"(c1), "r"(c2) : "memory");
}
__device__ __forceinline__ void tma3_red(const CUtensorMap* m, uint32_t src, int c0, int c1, int c2) {
    asm volatile("cp.reduce.async.bulk.tensor.3d.global.shared::cta.add.tile.bulk_group [%0, {%2, %3, %4}], [%1];"
                 ::"l"(m), "r"(src), "r"(c0), "r"(c1), "r"(c2) : "memory");
}

template <bool SCALE>
__device__ __forceinline__ void ln_pack(const Ctx& c, const float* a, const float2 cs, uint32_t& lo, uint32_t& hi) {
    if (SCALE) {
        lo = pack2(fmaf(c.m0, cs.x, a[0]) * c.r0, fmaf(c.m0, cs.y, a[1]) * c.r0);
        hi = pack2(fmaf(c.m1, cs.x, a[2]) * c.r1, fmaf(c.m1, cs.y, a[3]) * c.r1);
    } else {
        lo = pack2(fmaf(c.m0, cs.x, a[0]), fmaf(c.m0, cs.y, a[1]));
        hi = pack2(fmaf(c.m1, cs.x, a[2]), fmaf(c.m1, cs.y, a[3]));
    }
}
__host__ __device__ constexpr int qg_part(int i) { return i < 10 ? 1 : i < 20 ? 2 : 0; }
template <bool RF> __host__ __device__ constexpr int qg_main(int G) { return RF ? (G < 2 ? -1 - G : G - 2) : (G < 8 ? G : -1 - (G - 8)); }
template <bool RF> __host__ __device__ constexpr int qg_col(int i) {
    return qg_main<RF>(i % 10) >= 0 ? qg_part(i) * 64 + qg_main<RF>(i % 10) * 8 : 192 + qg_part(i) * 16 + (-1 - qg_main<RF>(i % 10)) * 8;
}
template <bool RF, int I0, int I1>
__device__ __forceinline__ void qkv_pre(const Ctx& c, float2 (&cs)[8]) {
#pragma unroll
    for (int i = I0; i < I1; i++) cs[i - I0] = lds64(c.sb + SM_CS + (qg_col<RF>(i) + 2 * c.q) * 4);
}
template <bool RF, int I0, int I1>
__device__ __forceinline__ void qkv_pack(const Ctx& c, const float2 (&cs)[8], const float (&a1)[96], const float (&a2)[24],
                                         uint32_t (&qp)[20], uint32_t (&kp)[20], uint32_t (&vp)[20]) {
#pragma unroll
    for (int i = I0; i < I1; i++) {
        const int P = qg_part(i), G = i % 10, M = qg_main<RF>(G);
        const float* a = (M >= 0) ? &a1[P * 32 + M * 4] : &a2[P * 8 + (-1 - M) * 4];
        if (P == 0) ln_pack<false>(c, a, cs[i - I0], qp[2 * G], qp[2 * G + 1]);
        else if (P == 1) ln_pack<true>(c, a, cs[i - I0], kp[2 * G], kp[2 * G + 1]);
        else ln_pack<true>(c, a, cs[i - I0], vp[2 * G], vp[2 * G + 1]);
    }
}

__device__ __forceinline__ void attn_prep(const Ctx& c, bool first, const uint32_t (&qp)[20], uint32_t (&qs)[4][2], float& nq) {
    const uint32_t lo = (c.q < 2) ? 0xffffffffu : 0u, hi = ~lo;
#pragma unroll
    for (int h = 0; h < 4; h++) {
        const int GS = (h < 2) ? 2 : 7;
        qs[h][0] = andv(qp[2 * GS], (h & 1) ? hi : lo);
        qs[h][1] = andv(qp[2 * GS + 1], (h & 1) ? hi : lo);
    }
    nq = __uint_as_float(movv(first ? 0xff800000u : 0u));
}
template <int H>
__device__ __forceinline__ void attn_logits(const uint32_t (&qp)[20], const uint32_t (&qs)[4][2], const uint32_t (&kp)[20],
                                            const uint32_t (&hk)[10], float nq, float (&sP)[4], float (&sL)[4], float (&sU)[4]) {
    constexpr int GA = (H == 0) ? 0 : (H == 1) ? 3 : (H == 2) ? 5 : 8;
    constexpr int GS = (H < 2) ? 2 : 7;
    mma16v(sP, qp[2 * GA], qp[2 * GA + 1], qp[2 * GA + 2], qp[2 * GA + 3], hk[GA], hk[GA + 1], nq, nq, nq, nq);
    mma16v(sL, qp[2 * GA], qp[2 * GA + 1], qp[2 * GA + 2], qp[2 * GA + 3], kp[2 * GA], kp[2 * GA + 2], 0.f, 0.f, 0.f, 0.f);
    mma16v(sU, qp[2 * GA], qp[2 * GA + 1], qp[2 * GA + 2], qp[2 * GA + 3], kp[2 * GA + 1], kp[2 * GA + 3], 0.f, 0.f, 0.f, 0.f);
    mma8v(sP, qs[H][0], qs[H][1], hk[GS]);
    mma8v(sL, qs[H][0], qs[H][1], kp[2 * GS]);
    mma8v(sU, qs[H][0], qs[H][1], kp[2 * GS + 1]);
}
__device__ __forceinline__ void attn_select(const Ctx& c, const float (&lg)[4][3][4], float (&s)[4][4]) {
    const bool gt0 = 2 * c.q > c.g, gt1 = 2 * c.q + 1 > c.g;
#pragma unroll
    for (int h = 0; h < 4; h++) {
        s[h][0] = gt0 ? lg[h][0][0] : lg[h][1][0];
        s[h][1] = gt1 ? lg[h][0][1] : lg[h][1][1];
        s[h][2] = gt0 ? lg[h][1][2] : lg[h][2][2];
        s[h][3] = gt1 ? lg[h][1][3] : lg[h][2][3];
    }
}
constexpr float kScale = 0.22360679774997896f * 1.4426950408889634f;
__device__ __forceinline__ void attn_max(const float (&s)[4][4], float (&m)[4][2]) {
#pragma unroll
    for (int h = 0; h < 4; h++) { m[h][0] = fmaxf(s[h][0], s[h][1]); m[h][1] = fmaxf(s[h][2], s[h][3]); }
#pragma unroll
    for (int o = 1; o < 4; o <<= 1) {
#pragma unroll
        for (int h = 0; h < 4; h++) {
            m[h][0] = fmaxf(m[h][0], __shfl_xor_sync(0xffffffffu, m[h][0], o));
            m[h][1] = fmaxf(m[h][1], __shfl_xor_sync(0xffffffffu, m[h][1], o));
        }
    }
}
__device__ __forceinline__ void attn_exp(const Ctx& c, float (&s)[4][4], float (&m)[4][2]) {
    constexpr float kf = SILU_TANH ? 2.f * kScale : -kScale / 1.4426950408889634f;
    const float k0 = kf * c.ga0, k1 = kf * c.ga1;
#pragma unroll
    for (int h = 0; h < 4; h++) {
        const float m0 = m[h][0] * -k0, m1 = m[h][1] * -k1;
        s[h][0] = ex2(fmaf(s[h][0], k0, m0)); s[h][1] = ex2(fmaf(s[h][1], k0, m0));
        s[h][2] = ex2(fmaf(s[h][2], k1, m1)); s[h][3] = ex2(fmaf(s[h][3], k1, m1));
        m[h][0] = s[h][0] + s[h][1]; m[h][1] = s[h][2] + s[h][3];
    }
}
__device__ __forceinline__ void attn_sum(float (&m)[4][2]) {
#pragma unroll
    for (int o = 1; o < 4; o <<= 1) {
#pragma unroll
        for (int h = 0; h < 4; h++) {
            m[h][0] += __shfl_xor_sync(0xffffffffu, m[h][0], o);
            m[h][1] += __shfl_xor_sync(0xffffffffu, m[h][1], o);
        }
    }
#pragma unroll
    for (int h = 0; h < 4; h++) { m[h][0] = rcp(m[h][0]); m[h][1] = rcp(m[h][1]); }
}
__device__ __forceinline__ void attn_probs(const Ctx& c, const float (&s)[4][4], const float (&m)[4][2], uint32_t (&p)[4][4]) {
    const uint32_t mk = ((2 * c.q > c.g) ? 0x0000ffffu : 0u) | ((2 * c.q + 1 > c.g) ? 0xffff0000u : 0u);
#pragma unroll
    for (int h = 0; h < 4; h++) {
        const uint32_t lo = pack2(s[h][0] * m[h][0], s[h][1] * m[h][0]), hi = pack2(s[h][2] * m[h][1], s[h][3] * m[h][1]);
        p[h][0] = andv(lo, mk); p[h][1] = andv(lo, ~mk); p[h][2] = andv(hi, mk); p[h][3] = andv(hi, ~mk);
    }
}
template <int I0, int I1, int N>
__device__ __forceinline__ void transpose_frags(uint32_t (&v)[N]) {
#pragma unroll
    for (int i = I0; i < I1; i++) v[i] = movm(v[i]);
}
template <int H>
__device__ __forceinline__ void attn_pv(const uint32_t (&p)[4], const uint32_t (&vp)[20], const uint32_t (&hv)[10], float (&o)[3][4]) {
    constexpr int GA = (H == 0) ? 0 : (H == 1) ? 3 : (H == 2) ? 5 : 8;
    constexpr int GS = (H < 2) ? 2 : 7;
#pragma unroll
    for (int t = 0; t < 3; t++) {
        const int G = (t < 2) ? GA + t : GS;
        mma16v(o[t], p[0], 0u, p[1], p[2], hv[G], vp[2 * G], 0.f, 0.f, 0.f, 0.f);
        mma8v(o[t], 0u, p[3], vp[2 * G + 1]);
    }
}
template <int H>
__device__ __forceinline__ void attn_pv_pack(const Ctx& c, const uint32_t (&p)[4], const uint32_t (&vp)[20], const uint32_t (&hv)[10], uint32_t (&op)[20]) {
    constexpr int GA = (H == 0) ? 0 : (H == 1) ? 3 : (H == 2) ? 5 : 8;
    constexpr int GS = (H < 2) ? 2 : 7;
    float o[3][4];
    attn_pv<H>(p, vp, hv, o);
#pragma unroll
    for (int t = 0; t < 2; t++) { op[2 * (GA + t)] = pack2(o[t][0], o[t][1]); op[2 * (GA + t) + 1] = pack2(o[t][2], o[t][3]); }
    const uint32_t lo = pack2(o[2][0], o[2][1]), hi = pack2(o[2][2], o[2][3]);
    if ((H & 1) == 0) { op[2 * GS] = lo; op[2 * GS + 1] = hi; }
    else { op[2 * GS] = (c.q >= 2) ? lo : op[2 * GS]; op[2 * GS + 1] = (c.q >= 2) ? hi : op[2 * GS + 1]; }
}
__device__ __forceinline__ void attn_pack(const Ctx& c, const float (&o)[4][3][4], uint32_t (&op)[20]) {
#pragma unroll
    for (int h = 0; h < 4; h++) {
        const int GA = (h == 0) ? 0 : (h == 1) ? 3 : (h == 2) ? 5 : 8;
#pragma unroll
        for (int t = 0; t < 2; t++) { op[2 * (GA + t)] = pack2v(o[h][t][0], o[h][t][1]); op[2 * (GA + t) + 1] = pack2v(o[h][t][2], o[h][t][3]); }
    }
    const bool even = c.q < 2;
#pragma unroll
    for (int hp = 0; hp < 2; hp++) {
        const int GS = hp ? 7 : 2;
        const float* e = o[2 * hp][2];
        const float* d = o[2 * hp + 1][2];
        op[2 * GS] = pack2v(even ? e[0] : d[0], even ? e[1] : d[1]);
        op[2 * GS + 1] = pack2v(even ? e[2] : d[2], even ? e[3] : d[3]);
    }
}

__device__ __forceinline__ void swiglu_consts(Ctx& c, float r0, float r1) {
    c.ga0 = 0.5f * r0; c.ga1 = 0.5f * r1; c.gb0 = c.ga0 * r0; c.gb1 = c.ga1 * r1;
}
__device__ __forceinline__ uint32_t piece_off() {
    const uint32_t t = launder(threadIdx.x);
    const uint32_t row = (t >> 7) * 64 + ((t >> 5) & 3) * 16 + ((t & 31) >> 2);
    return row * 64 + (((t & 3) ^ ((row >> 1) & 3)) << 4);
}
#define PIECE_OFF(c) ((c).aoff)
__device__ __forceinline__ uint8_t* act_piece(const Ctx& c, int tile) { return g_act + (size_t)tile * (34 * 16384) + PIECE_OFF(c); }
__device__ __forceinline__ void stg128(uint8_t* p, uint32_t a, uint32_t b, uint32_t c, uint32_t d) {
    asm volatile("st.global.v4.b32 [%0], {%1, %2, %3, %4};" ::"l"(p), "r"(a), "r"(b), "r"(c), "r"(d) : "memory");
}
__device__ __forceinline__ void stg64(uint8_t* p, uint32_t a, uint32_t b) {
    asm volatile("st.global.v2.b32 [%0], {%1, %2};" ::"l"(p), "r"(a), "r"(b) : "memory");
}

__device__ __forceinline__ void o_store(const Ctx& c, int tile, int slot, const uint32_t (&op)[20]) {
    uint8_t* odst = act_piece(c, tile) + 5 * (slot >> 1) * 8192;
    if ((slot & 1) == 0) {
        stg128(odst, op[0], op[2], op[4], op[6]);
        stg128(odst + 512, op[1], op[3], op[5], op[7]);
        stg128(odst + 8192, op[8], op[10], op[12], op[14]);
        stg128(odst + 8192 + 512, op[9], op[11], op[13], op[15]);
        stg64(odst + 16384, op[16], op[18]);
        stg64(odst + 16384 + 512, op[17], op[19]);
    } else {
        stg64(odst + 16384 + 8, op[0], op[2]);
        stg64(odst + 16384 + 512 + 8, op[1], op[3]);
        stg128(odst + 24576, op[4], op[6], op[8], op[10]);
        stg128(odst + 24576 + 512, op[5], op[7], op[9], op[11]);
        stg128(odst + 32768, op[12], op[14], op[16], op[18]);
        stg128(odst + 32768 + 512, op[13], op[15], op[17], op[19]);
    }
}

__device__ __forceinline__ void swiglu_group(const Ctx& c, const float (&acc)[64], int G, const float2 cg, const float2 cu, uint32_t& lo, uint32_t& hi) {
    float h[4];
#pragma unroll
    for (int e = 0; e < 4; e++) {
        const float m = (e < 2) ? c.m0 : c.m1, ga = (e < 2) ? c.ga0 : c.ga1, gb = (e < 2) ? c.gb0 : c.gb1;
        const float gate = fmaf(m, (e & 1) ? cg.y : cg.x, acc[4 * G + e]), up = fmaf(m, (e & 1) ? cu.y : cu.x, acc[32 + 4 * G + e]);
        h[e] = (gate * up) * fmaf(tanh_fast(gate * ga), gb, gb);
    }
    lo = pack2(h[0], h[1]);
    hi = pack2(h[2], h[3]);
}
template <int F, int G0, int G1>
__device__ __forceinline__ void swiglu_pre(const Ctx& c, float2 (&cs)[8]) {
#pragma unroll
    for (int G = G0; G < G1; G++) {
        cs[2 * (G - G0)] = lds64(c.sb + sm_csb(F) + (8 * G + 2 * c.q) * 4);
        cs[2 * (G - G0) + 1] = lds64(c.sb + sm_csb(F) + 256 + (8 * G + 2 * c.q) * 4);
    }
}
template <int F, int G0, int G1, int NPRE>
__device__ __forceinline__ void swiglu_groups(const Ctx& c, const float (&acc)[64], const float2 (&cs)[8], uint32_t (&hp)[8], uint8_t* hdst,
                                              uint32_t sdst = 0) {
#pragma unroll
    for (int G = G0; G < G1; G++) {
        const float2 cg = (G - G0 < NPRE) ? cs[2 * (G - G0)] : lds64(c.sb + sm_csb(F) + (8 * G + 2 * c.q) * 4);
        const float2 cu = (G - G0 < NPRE) ? cs[2 * (G - G0) + 1] : lds64(c.sb + sm_csb(F) + 256 + (8 * G + 2 * c.q) * 4);
        swiglu_group(c, acc, G, cg, cu, hp[G & 3], hp[4 + (G & 3)]);
        if ((G & 3) == 3) {
            if (F >= 1) {
                sts128(sdst + (G >> 2) * 8192, make_uint4(hp[0], hp[1], hp[2], hp[3]));
                sts128(sdst + (G >> 2) * 8192 + 512, make_uint4(hp[4], hp[5], hp[6], hp[7]));
            } else {
                stg128(hdst + (G >> 2) * 8192, hp[0], hp[1], hp[2], hp[3]);
                stg128(hdst + (G >> 2) * 8192 + 512, hp[4], hp[5], hp[6], hp[7]);
            }
        }
    }
}
template <int F>
__device__ __forceinline__ uint32_t own_piece(const Ctx& c) { return c.sb + (F == 1 ? SM_X : SM_OWN) + PIECE_OFF(c); }
template <int F>
__device__ __forceinline__ void own_done(const Ctx& c) {
    asm volatile("fence.proxy.async.shared::cta;" ::: "memory");
    arrive_local(c, B_WDONE + 1 + F);
}

template <int N>
__device__ __forceinline__ void f_issue(const Ctx& c, float (&acc)[64]) {
    constexpr int S = (N - 20) % 10, SLOT = N & 3;
    if (threadIdx.x < 32) TRACEF(192 + N);
    mbar_wait(c.bar + (B_RFULL + SLOT) * 8, (N >> 2) & 1);
    if (threadIdx.x < 32) TRACEF(64 + N);
    wg_fence();
#pragma unroll
    for (int kk = 0; kk < 4; kk++)
        wgmma_n128(acc, c.a_lo + S * 1024 + kk * 2, HI_128, c.b_lo + lbo(8192) + SLOT * 1024 + kk * 128, HI_128, (S | kk) != 0);
    wg_commit();
    wg_wait<1>();
    if (N - 1 <= 45) arrive_both(c, B_REMPTY + ((N - 1) & 3));
    if (N == 43) { mbar_wait(c.bar + B_INIT * 8, 0); arrive_both(c, B_GEMPTY + 0); }
    if (N == 45) arrive_both(c, B_GEMPTY + 1);
    if (N == 48) arrive_both(c, B_GEMPTY + 2);
}

__device__ __forceinline__ void block_edge(const Ctx& c) { mbar_wait(c.bar + B_CS * 8, 0); }

template <bool RF>
__device__ __forceinline__ void q_epilogue(const Ctx& c, float2 (&cs)[8], const float (&q1)[96], const float (&q2)[24], uint32_t (&qp)[20],
                                           uint32_t (&kp)[20], uint32_t (&vp)[20], float (&accA)[64], bool hst, uint8_t* hq_st) {
    qkv_pre<RF, 0, 4>(c, cs);   f_issue<23>(c, accA); if (EDGE_AFTER & 4) block_edge(c); qkv_pack<RF, 0, 4>(c, cs, q1, q2, qp, kp, vp);
    qkv_pre<RF, 4, 8>(c, cs);   f_issue<24>(c, accA); qkv_pack<RF, 4, 8>(c, cs, q1, q2, qp, kp, vp);
    if (hst) stg128(hq_st, kp[1], kp[3], kp[7], kp[9]);
    qkv_pre<RF, 8, 12>(c, cs);  f_issue<25>(c, accA); qkv_pack<RF, 8, 12>(c, cs, q1, q2, qp, kp, vp);
    if (hst) { stg128(hq_st + 512, kp[11], kp[13], kp[17], kp[19]); stg128(hq_st + 1024, kp[5], kp[15], vp[1], vp[3]); }
    qkv_pre<RF, 12, 16>(c, cs); f_issue<26>(c, accA); qkv_pack<RF, 12, 16>(c, cs, q1, q2, qp, kp, vp);
    if (hst) stg128(hq_st + 1536, vp[5], vp[7], vp[9], vp[11]);
    qkv_pre<RF, 16, 20>(c, cs); f_issue<27>(c, accA); qkv_pack<RF, 16, 20>(c, cs, q1, q2, qp, kp, vp);
    if (hst) stg128(hq_st + 2048, vp[13], vp[15], vp[17], vp[19]);
    __syncwarp();
    if (c.lane == 0) {
        mbar_arrive(c.bar + (B_HALOR + c.par) * 8);
        if (c.w == 3) mbar_arrive(c.bar + B_HALOW * 8);
    }
    qkv_pre<RF, 20, 25>(c, cs); f_issue<28>(c, accA); qkv_pack<RF, 20, 25>(c, cs, q1, q2, qp, kp, vp);
    transpose_frags<0, 10>(vp);
    qkv_pre<RF, 25, 30>(c, cs); arrive_local(c, B_CSFREE); f_issue<29>(c, accA); qkv_pack<RF, 25, 30>(c, cs, q1, q2, qp, kp, vp);
    transpose_frags<10, 20>(vp);
}

struct AccG {
    float v[80];
    __device__ __forceinline__ float operator[](int i) const { return v[i]; }
};
__device__ __forceinline__ void g_issue(const Ctx& c, AccG& acc, int slot, int parity, bool first, int t, bool own = false) {
    if (threadIdx.x < 32) TRACEFG(250 + t);
    if (first) mbar_wait(c.bar + (B_WDONE + 2) * 8, 0);
    if (own) mbar_wait(c.bar + (B_WDONE + 3) * 8, 0);
    mbar_wait(c.bar + (B_GFULL + slot) * 8, parity);
    if (threadIdx.x < 32) TRACEFG(120 + t);
    wg_fence();
    const uint32_t s0 = (c.sb & 0x3FFFF) >> 4, st = s0 + slot * (G_STAGE >> 4);
    const uint32_t alo = (own ? s0 + (SM_OWN >> 4) : st) + c.par * 256 + lbo(16), blo = st + 1024 + lbo(4096);
#pragma unroll
    for (int kk = 0; kk < 4; kk++) {
        wgmma_n160(acc.v, alo + (kk >> 1) * 512 + (kk & 1) * 2, HI_64, blo + (kk >> 1) * 768 + (kk & 1) * 128, HI_128, !(first && kk == 0));
    }
    wg_commit();
}

template <int N, int BIT, int M>
__device__ __forceinline__ void halve(float (&acc)[M], int lane) {
    const bool up = lane & BIT;
#pragma unroll
    for (int e = 0; e < N; e++) {
        const float lo = acc[e], hi = acc[e + N];
        const float send = up ? lo : hi, keep = up ? hi : lo;
        acc[e] = keep + __shfl_xor_sync(0xffffffffu, send, BIT);
    }
}
template <int O, int M>
__device__ __forceinline__ void acc8(float (&acc)[M], const uint4& v) {
    acc[O + 0] += bf_lo(v.x); acc[O + 1] += bf_hi(v.x); acc[O + 2] += bf_lo(v.y); acc[O + 3] += bf_hi(v.y);
    acc[O + 4] += bf_lo(v.z); acc[O + 5] += bf_hi(v.z); acc[O + 6] += bf_lo(v.w); acc[O + 7] += bf_hi(v.w);
}
__device__ __forceinline__ uint4 ldg_nc(const void* p) {
    uint4 v; asm volatile("ld.global.nc.v4.u32 {%0,%1,%2,%3}, [%4];" : "=r"(v.x), "=r"(v.y), "=r"(v.z), "=r"(v.w) : "l"(p)); return v;
}

constexpr uint32_t H_BUF = 32768, H_RED = 6 * H_BUF;
constexpr int H_FULL = 0, H_EMPTY = 6;
__device__ __forceinline__ uint4 f4_bits(float a, float b, float c, float d) {
    return make_uint4(__float_as_uint(a), __float_as_uint(b), __float_as_uint(c), __float_as_uint(d));
}
__device__ __forceinline__ void helper_cta(int h, uint32_t sb, const Maps& maps, const __nv_bfloat16* wqkv,
                                           const __nv_bfloat16* wo, const __nv_bfloat16* w2) {
    const int t = threadIdx.x, warp = __shfl_sync(0xffffffffu, t >> 5, 0), lane = t & 31;
    const uint32_t bar = sb + SM_BAR;
    if (t == 0) {
        for (int i = 0; i < 6; i++) { mbar_init(bar + (H_FULL + i) * 8, 1); mbar_init(bar + (H_EMPTY + i) * 8, 8); }
        asm volatile("fence.mbarrier_init.release.cluster;" ::: "memory");
    }
    __syncthreads();
    if (warp == 11) {
        const CUtensorMap* mc = (h >> 1) ? &maps.w3c : &maps.w1c;
        int s = 0, ph = 1;
#pragma unroll 1
        for (int i = 0; i < 50; i++) {
            mbar_wait(bar + (H_EMPTY + s) * 8, ph);
            if (elect_one()) {
                if (i < 20) {
                    mbar_expect_tx(bar + (H_FULL + s) * 8, 32768);
                    tma2(sb + s * H_BUF, &maps.wqc, 512 * h + 256 * (i & 1), 64 * (JOBA_REV ? 9 - (i >> 1) : (i >> 1)), bar + (H_FULL + s) * 8);
                } else {
                    const int f = (i - 20) / 10, r = (i - 20) % 10;
                    mbar_expect_tx(bar + (H_FULL + s) * 8, 32768);
                    tma2(sb + s * H_BUF, mc, 512 * f + 256 * (r & 1), 320 * (h & 1) + 64 * (r >> 1), bar + (H_FULL + s) * 8);
                }
            }
            if (++s == 6) { s = 0; ph ^= 1; }
        }
        return;
    }
    if (warp >= 8) return;
    const unsigned tag = ld_relaxed(&g_cntO[0]) / 8 + 1;
    int s = 0, ph = 0;
#pragma unroll 1
    for (int job = 0; job < 4; job++) {
        float acc[2][8];
#pragma unroll
        for (int e = 0; e < 8; e++) acc[0][e] = acc[1][e] = 0.f;
#pragma unroll 1
        for (int rb = 0; rb < (job ? 5 : 10); rb++) {
#pragma unroll
            for (int ch = 0; ch < 2; ch++) {
                mbar_wait(bar + (H_FULL + s) * 8, ph);
                uint4 v[8];
#pragma unroll
                for (int r = 0; r < 8; r++) v[r] = lds128(sb + s * H_BUF + (warp * 8 + r) * 512 + lane * 16);
#pragma unroll
                for (int r = 0; r < 8; r++) acc8<0>(acc[ch], v[r]);
                __syncwarp();
                if (lane == 0) mbar_arrive(bar + (H_EMPTY + s) * 8);
                if (++s == 6) { s = 0; ph ^= 1; }
            }
        }
#pragma unroll
        for (int ch = 0; ch < 2; ch++) {
            sts128(sb + H_RED + (warp * 512 + ch * 256 + lane * 8) * 4, f4_bits(acc[ch][0], acc[ch][1], acc[ch][2], acc[ch][3]));
            sts128(sb + H_RED + (warp * 512 + ch * 256 + lane * 8 + 4) * 4, f4_bits(acc[ch][4], acc[ch][5], acc[ch][6], acc[ch][7]));
        }
        bar_sync<1, 256>();
        {
            float s0 = 0.f, s1 = 0.f;
#pragma unroll
            for (int r = 0; r < 8; r++) { const float2 v = lds64(sb + H_RED + (r * 512 + 2 * t) * 4); s0 += v.x; s1 += v.y; }
            if (job == 0) { if (512 * h + 2 * t < 1920) st_tag2(&g_csA[512 * h + 2 * t], tagged(tag, s0), tagged(tag, s1)); }
            else st_tag2(&g_csB[((h & 1) * 2 + (h >> 1)) * kF + 512 * (job - 1) + 2 * t], tagged(tag, s0), tagged(tag, s1));
        }
        bar_sync<1, 256>();
        if (warp == 0) TRACE(job == 0 ? 25 : 29 + job);
    }
#pragma unroll 1
    for (int k = h * 256 + t; k < 6400 + 15360; k += 4 * 256) {
        const __nv_bfloat16* p = (k < 6400) ? wo + (size_t)k * 64 : w2 + (size_t)(k - 6400) * 64;
        asm volatile("prefetch.global.L2 [%0];" ::"l"(p));
    }
}

}

__global__ void __cluster_dims__(2, 1, 1) __launch_bounds__(384, 1)
fused_block_kernel(const __grid_constant__ Maps maps, const __nv_bfloat16* __restrict__ x, const __nv_bfloat16* __restrict__ wqkv,
                   const __nv_bfloat16* __restrict__ w1, const __nv_bfloat16* __restrict__ w3,
                   const __nv_bfloat16* __restrict__ wo, const __nv_bfloat16* __restrict__ w2, __nv_bfloat16* __restrict__ out) {
    extern __shared__ __align__(1024) uint8_t smem_raw[];
    const uint32_t sb = smem_u32(smem_raw);
    const int warp = __shfl_sync(0xffffffffu, threadIdx.x >> 5, 0);
    const int lane = threadIdx.x & 31;
    uint32_t rank;
    asm("mov.u32 %0, %%cluster_ctarank;" : "=r"(rank));
    const int b = blockIdx.x;
    if (b >= 128) {
        if (threadIdx.x == 0) TRACE(0);
        helper_cta(b - 128, sb, maps, wqkv, wo, w2);
        return;
    }
    const int pair = b >> 1;
    const int slot = (pair + SLOT_ROT) & 7;
    const int tile = (pair >> 3) * 2 + rank;
    const int jj = slot >> 1;
    const int half = (slot ^ (slot >> 1)) & 1;
    const int own_i = 2 * (slot >> 2) + ((slot & 3) >> 1);
    auto hslot = [&](int i) { return 4 * ((i >> 1) & 1) + (half ? 1 + (i & 1) : 3 * (i & 1)); };
    const bool rf = RF_ALIGN && (slot & 3) == 3;
    const int wcol = 80 * slot + (rf ? 16 : 0), wcolr = 80 * slot + (rf ? 0 : 64);

    if (threadIdx.x == 0) TRACE(0);
    if (warp < 2) {
        const int i = warp * 32 + lane;
        if (i < 48) asm volatile("prefetch.global.L2 [%0];" ::"l"(x + (size_t)(tile * 128 + slot * 16 + i / 3) * kD + (i % 3) * 64));
    } else if (warp == 2) {
        if (lane < 30) asm volatile("prefetch.global.L2 [%0];" ::"l"(wqkv + (size_t)b * 1920 + lane * 64));
    }
    if (warp == 8) {
        TRACEG(62);
        if (elect_one()) {
#pragma unroll
            for (int i = B_RFULL; i < B_GFULL; i++) mbar_init(sb + SM_BAR + i * 8, bar_count(i));
#pragma unroll
            for (int i = 0; i < 3; i++) mbar_init(sb + SM_BAR + (B_XFULL + i) * 8, 1);
            asm volatile("fence.mbarrier_init.release.cluster;" ::: "memory");
        }
        __syncwarp();
        TRACE(22);
    }
    asm volatile("barrier.cluster.arrive.relaxed.aligned;" ::: "memory");
    if (warp == 8) {
        if (elect_one()) {
            mbar_expect_tx(sb + SM_BAR + B_XFULL * 8, 16384);
            tma3(sb + SM_X, &maps.x, 0, tile * 64, 0, sb + SM_BAR + B_XFULL * 8);
        }
        __syncwarp();
    } else if (warp == 9) {
        if (elect_one()) {
#pragma unroll
            for (int i = B_XFULL + 3; i < B_RFULL; i++) mbar_init(sb + SM_BAR + i * 8, bar_count(i));
#pragma unroll
            for (int i = B_GFULL; i < B_GFULL + 7; i++) mbar_init(sb + SM_BAR + i * 8, bar_count(i));
            asm volatile("fence.mbarrier_init.release.cluster;" ::: "memory");
        }
        __syncwarp();
    } else if (warp == 10) {
        if (elect_one()) {
#pragma unroll
            for (int i = B_GFULL + 7; i < B_WDONE + 1; i++) mbar_init(sb + SM_BAR + i * 8, bar_count(i));
            asm volatile("fence.mbarrier_init.release.cluster;" ::: "memory");
        }
        __syncwarp();
    } else if (warp == 11) {
        if (elect_one()) {
#pragma unroll
            for (int i = B_WDONE + 1; i < B_COUNT; i++) mbar_init(sb + SM_BAR + i * 8, bar_count(i));
            asm volatile("fence.mbarrier_init.release.cluster;" ::: "memory");
        }
        __syncwarp();
    }
    asm volatile("barrier.cluster.wait.aligned;" ::: "memory");
    if (warp == 8) {
        TRACE(24);
        if (elect_one()) {
#pragma unroll
            for (int n = 0; n < 4; n++) {
                const uint32_t fb = sb + SM_BAR + (B_RFULL + n) * 8;
                mbar_expect_tx(fb, 15360);
                tma3_mc(sb + SM_RING + n * 16384 + rank * 6144, &maps.wq, wcol, 32 * n + 16 * rank, 0, fb);
                tma3_mc(sb + SM_RING + n * 16384 + 12288 + rank * 1536, &maps.wqr, wcolr, 32 * n + 16 * rank, 0, fb);
                if (n & 1) {
                    const int c = (n + 1) / 2;
                    mbar_expect_tx(sb + SM_BAR + (B_XFULL + c) * 8, 16384);
                    tma3(sb + SM_X + c * 16384, &maps.x, c * 64, tile * 64, 0, sb + SM_BAR + (B_XFULL + c) * 8);
                }
            }
        }
        __syncwarp();
        TRACE(1);
    }
    __syncthreads();

    if (warp >= 8) {
        asm volatile("setmaxnreg.dec.sync.aligned.u32 56;");
        const uint32_t bar = launder(sb + SM_BAR);
        const int n0 = half ? 8 - NH0 : NH0;
        auto g_load = [&](int t, int s, int ph, int part) {
            const int u = t - 1 - n0;
            const int kc = (t == 0) ? 18 + slot : (u < 0) ? 10 + NH0 * half + t - 1 : (u < 5) ? 5 * half + u
                         : (u < 8) ? 18 + hslot(own_i + u - 4) : 26 + hslot(own_i + u - 8);
            const int flag = (t == 1) ? 0 : (u == 0) ? 1 : (u >= 5 && u < 8) ? u - 3 : (u >= 9) ? u - 4 : -1;
            const bool own = (t == 0) || (u == 8);
            const uint32_t st = sb + s * G_STAGE, fb = bar + (B_GFULL + s) * 8;
            if (part & 1) {
                mbar_wait(bar + (B_GEMPTY + s) * 8, ph);
                TRACEP(280 + t);
                if (elect_one()) {
                    const bool isO = kc < 10;
                    const int a0 = ((isO ? kc : kc - 10) * 2 + rank) * 4;
                    mbar_expect_tx(fb, own ? 20480 : 16384 + 20480);
                    tma5_mc(st + 16384 + rank * 12288, isO ? &maps.wo2 : &maps.w22, 160 * jj + G_ALIGN * 32 * (jj & 1), a0, fb);
                    tma4_mc(st + 16384 + rank * 12288 + 8192, isO ? &maps.wo1 : &maps.w21, 160 * jj + ((G_ALIGN && (jj & 1)) ? 0 : 128), a0, fb);
                }
            }
            if ((part & 2) && !own) {
                if (flag >= 0) mbar_wait(bar + (B_FLAG + flag) * 8, 0);
                if (t == 5) mbar_wait(bar + B_H1OUT * 8, 0);
                TRACEP(300 + t);
                if (elect_one()) bulk_g2s(st, g_act + (size_t)(tile * 34 + kc) * 16384, 16384, fb);
            }
        };
        if (warp == 8) {
            const uint32_t ring = launder(sb + SM_RING);
#pragma unroll 1
            for (int n = 4; n < 20; n++) {
                const int s = n & 3;
                mbar_wait(bar + (B_REMPTY + s) * 8, ((n >> 2) - 1) & 1);
                TRACEP(140 + n);
                const int c = (n == 4) ? 3 : (n <= 15 && (n & 1)) ? (n + 3) / 2 : 0;
                if (elect_one()) {
                    mbar_expect_tx(bar + (B_RFULL + s) * 8, 15360);
                    tma3_mc(ring + s * 16384 + rank * 6144, &maps.wq, wcol, 32 * n + 16 * rank, 0, bar + (B_RFULL + s) * 8);
                    tma3_mc(ring + s * 16384 + 12288 + rank * 1536, &maps.wqr, wcolr, 32 * n + 16 * rank, 0, bar + (B_RFULL + s) * 8);
                    if (c > 0) {
                        mbar_expect_tx(bar + (B_XFULL + c) * 8, 16384);
                        tma3(sb + SM_X + c * 16384, &maps.x, c * 64, tile * 64, 0, bar + (B_XFULL + c) * 8);
                    }
                }
            }
            const CUtensorMap* mf = rank ? &maps.w3 : &maps.w1;
            {
                int col = 64 * slot, k = 0;
#pragma unroll 1
                for (int n = 20; n < 50; n++) {
                    const int s = n & 3;
                    mbar_wait(bar + (B_REMPTY + s) * 8, ((n >> 2) - 1) & 1);
                    TRACEP(140 + n);
                    if (elect_one()) {
                        mbar_expect_tx(bar + (B_RFULL + s) * 8, 16384);
                        tma2_mc(ring + s * 16384 + rank * 8192, mf, col, k, bar + (B_RFULL + s) * 8);
                    }
                    k += 64;
                    if (k == 640) { k = 0; col += 512; }
                }
            }
            TRACE(2);
            constexpr int T1 = 2;
            int s = T1, ph = 0;
            const int nt = 13 + n0;
#pragma unroll 1
            for (int t = T1; t < nt; t++) {
                g_load(t, s, ph, 3);
                if (++s == 5) { s = 0; ph ^= 1; }
            }
            TRACE(3);
        } else {
            const int a = warp - 9;
            const unsigned tag = ld_relaxed(&g_cntO[tile * 32]) / 8 + 1;
            if (a == 0) {
                mbar_wait(bar + (B_XFULL + CS_WAIT) * 8, 0);
                {
                    const int n0 = 4 * lane, n1 = 128 + 4 * (lane < 28 ? lane : 27);
                    const unsigned* p0 = &g_csA[(n0 >> 6) * kD + wcol + (n0 & 63)];
                    const unsigned* p1 = &g_csA[(n1 < 192) ? 2 * kD + wcol + (n1 & 63) : ((n1 - 192) >> 4) * kD + wcolr + ((n1 - 192) & 15)];
                    uint4 v0, v1;
                    gather2(p0, p1, tag, v0, v1);
                    sts128(sb + SM_CS + lane * 16, f4_bits(tag_val(v0.x), tag_val(v0.y), tag_val(v0.z), tag_val(v0.w)));
                    if (lane < 28) sts128(sb + SM_CS + 512 + lane * 16, f4_bits(tag_val(v1.x), tag_val(v1.y), tag_val(v1.z), tag_val(v1.w)));
                    __syncwarp();
                    if (lane == 0) mbar_arrive(bar + B_CS * 8);
                }
                TRACE(5);
                mbar_wait(bar + B_HALOW * 8, 0);
                if (lane == 0) {
                    if (tile < 15) { fence_gpu(); st_relaxed(&g_flagHalo[(tile * 8 + slot) * 32], tag); }
                    if (tile > 0) poll_ge(&g_flagHalo[((tile - 1) * 8 + slot) * 32], tag);
                    mbar_arrive(bar + B_HALOR * 8);
                    mbar_arrive(bar + (B_HALOR + 1) * 8);
                    TRACE(28);
                }
                __syncwarp();
                poll_multi(&g_cntH[tile * 32], tag * 8, bar + (B_FLAG + 0) * 8, lane == 0); TRACE(44);
                const unsigned* fl = &g_flagH[(tile * 8 + hslot(own_i + lane + 1)) * 32];
                poll_multi(lane < 3 ? fl : &g_cntO[tile * 32], lane < 3 ? tag : tag * 8, bar + (lane < 3 ? B_FLAG + 2 + lane : B_FLAG + 1) * 8, lane < 4);
                TRACE(45); TRACE(46); TRACEG(50);
                poll_multi(fl + 16 * 8 * 32, tag, bar + (B_FLAG + 5 + (lane & 3)) * 8, lane < 3);
                TRACE(47); TRACEG(53);
            } else {
                {
                    const int t = 16 * slot + 8 * (a - 1) + (lane >> 2);
                    const uint32_t rowa = sb + SM_X + ((t & 1) * 64 + (t >> 1)) * 128 + (lane & 3) * 32;
                    float x0 = 0.f, s4[4] = {0.f, 0.f, 0.f, 0.f}, q4[4] = {0.f, 0.f, 0.f, 0.f};
#pragma unroll 1
                    for (int c = 0; c < 10; c++) {
                        mbar_wait(bar + (B_XFULL + c) * 8, 0);
                        const uint4 v0 = lds128(rowa + c * 16384), v1 = lds128(rowa + c * 16384 + 16);
                        if (c == 0) x0 = __shfl_sync(0xffffffffu, bf_lo(v0.x), lane & 28);
                        const uint32_t wv[8] = {v0.x, v0.y, v0.z, v0.w, v1.x, v1.y, v1.z, v1.w};
#pragma unroll
                        for (int e = 0; e < 8; e++) {
                            const float d0 = bf_lo(wv[e]) - x0, d1 = bf_hi(wv[e]) - x0;
                            s4[e & 3] += d0; q4[e & 3] = fmaf(d0, d0, q4[e & 3]);
                            s4[e & 3] += d1; q4[e & 3] = fmaf(d1, d1, q4[e & 3]);
                        }
                    }
                    float ss = (q4[0] + q4[1]) + (q4[2] + q4[3]), sm = (s4[0] + s4[1]) + (s4[2] + s4[3]);
#pragma unroll
                    for (int o = 1; o < 4; o <<= 1) { sm += __shfl_xor_sync(0xffffffffu, sm, o); ss += __shfl_xor_sync(0xffffffffu, ss, o); }
                    if ((lane & 3) == 0) {
                        const float dm = sm * (1.f / kD), var = fmaxf(ss * (1.f / kD) - dm * dm, 0.f);
                        st_tag2(&g_stats[(tile * 128 + t) * 2], tagged(tag, rsqrtf(var + 1e-5f)), tagged(tag, x0 + dm));
                    }
                    if (a == 1) TRACE(26);
                }
                if (a == 2) {
                    uint4 v0, v1;
                    gather2(&g_stats[(tile * 128 + 2 * lane) * 2], &g_stats[(tile * 128 + 64 + 2 * lane) * 2], tag, v0, v1);
                    asm volatile("st.shared.v2.f32 [%0], {%1,%2};" ::"r"(sb + SM_ST + lane * 8), "f"(tag_val(v0.x)), "f"(-tag_val(v0.y)) : "memory");
                    asm volatile("st.shared.v2.f32 [%0], {%1,%2};" ::"r"(sb + SM_ST + (64 + lane) * 8), "f"(tag_val(v0.z)), "f"(-tag_val(v0.w)) : "memory");
                    asm volatile("st.shared.v2.f32 [%0], {%1,%2};" ::"r"(sb + SM_ST + (32 + lane) * 8), "f"(tag_val(v1.x)), "f"(-tag_val(v1.y)) : "memory");
                    asm volatile("st.shared.v2.f32 [%0], {%1,%2};" ::"r"(sb + SM_ST + (96 + lane) * 8), "f"(tag_val(v1.z)), "f"(-tag_val(v1.w)) : "memory");
                    __syncwarp();
                    if (lane == 0) mbar_arrive(bar + B_ST * 8);
                    TRACE(6);
#pragma unroll 1
                    for (int r = 0; r < 2; r++) {
                        mbar_wait(bar + (B_WDONE + r) * 8, 0);
                        TRACE(36 + r);
                        if (lane == 0) { fence_gpu(); red_add(r ? &g_cntO[tile * 32] : &g_cntH[tile * 32], 1); }
                        __syncwarp();
                        TRACE(40 + r);
                    }
#pragma unroll 1
                    for (int r = 2; r < 4; r++) {
                        mbar_wait(bar + (B_WDONE + r) * 8, 0);
                        TRACE(36 + r); TRACEG(r == 2 ? 48 : 51);
                        if (elect_one()) {
                            asm volatile("cp.async.bulk.global.shared::cta.bulk_group [%0], [%1], %2;"
                                         ::"l"(g_act + (size_t)(tile * 34 + 2 + 8 * r + slot) * 16384), "r"(sb + (r == 2 ? SM_X : SM_OWN)), "r"(16384) : "memory");
                            asm volatile("cp.async.bulk.commit_group;" ::: "memory");
                            asm volatile("cp.async.bulk.wait_group 0;" ::: "memory");
                            st_relaxed(&g_flagH[((r - 2) * 128 + tile * 8 + slot) * 32], tag);
                            if (r == 2) mbar_arrive(bar + B_H1OUT * 8);
                        }
                        __syncwarp();
                        TRACE(40 + r); TRACEG(r == 2 ? 49 : 52);
                    }
                } else {
#pragma unroll 1
                    for (int f = 0; f < 3; f++) {
                        uint4 v, w;
                        int it = 0;
#pragma unroll 1
                        while (true) {
                            v = ld_tag4(&g_csB[(lane >> 4) * kF + 512 * f + 64 * slot + 4 * (lane & 15)]);
                            w = ld_tag4(&g_csB[(2 + (lane >> 4)) * kF + 512 * f + 64 * slot + 4 * (lane & 15)]);
                            if (__all_sync(0xffffffffu, tag_ok(v, tag) && tag_ok(w, tag)) || ++it > (1 << 15)) break;
                        }
                        if (f == 1) mbar_wait(bar + B_CSFREE * 8, 0);
                        sts128(sb + (f == 0 ? SM_CSB0 : SM_CS + (f - 1) * 512) + lane * 16,
                               f4_bits(tag_val(v.x) + tag_val(w.x), tag_val(v.y) + tag_val(w.y), tag_val(v.z) + tag_val(w.z), tag_val(v.w) + tag_val(w.w)));
                        __syncwarp();
                        if (lane == 0) mbar_arrive(bar + (B_CSB + f) * 8);
                        TRACE(33 + f);
                        if (f == 0) {
#pragma unroll 1
                            for (int i = 0; i < 10; i++) {
                                const int p = slot * 10 + i, xc = p >> 3, pi = p & 7;
                                if (elect_one()) tma3_store(&maps.o64, sb + SM_X + xc * 16384 + pi * 2048, 64 * xc, tile * 64 + 16 * (pi & 3), pi >> 2);
                                const long long t0 = clock64();
                                while (clock64() - t0 < INIT_GAP) { }
                            }
                            if (elect_one()) {
                                asm volatile("cp.async.bulk.commit_group;" ::: "memory");
                                asm volatile("cp.async.bulk.wait_group 0;" ::: "memory");
                                asm volatile("fence.proxy.async;" ::: "memory");
                                mbar_arrive(bar + (B_WDONE + 1) * 8);
                                mbar_arrive(bar + B_INIT * 8);
                            }
                            TRACE(7);
                        }
                    }
#pragma unroll 1
                    for (int i = 0; i < 4; i++) {
                        g_load(i >> 1, i >> 1, 0, 1 + (i & 1));
                        spin(G_AUX_GAP);
                    }
                }
            }
        }
    } else {
        asm volatile("setmaxnreg.inc.sync.aligned.u32 224;");
        Ctx c;
        c.sb = sb;
        c.bar = sb + SM_BAR;
        c.lane = lane; c.q = lane & 3; c.g = lane >> 2; c.w = warp & 3; c.par = warp >> 2;
        c.rbar = mapa(c.bar, lane & 1);
        c.a_lo = ((sb & 0x3FFFF) >> 4) + c.par * 512 + lbo(16);
        c.b_lo = ((sb + SM_RING) & 0x3FFFF) >> 4;
        const int idx0 = c.w * 16 + c.g;
        c.aoff = piece_off();

        float q1[96], q2[24];
#pragma unroll
        for (int n = 0; n < 20; n++) {
            if (warp == 0) TRACEF(192 + n);
            if ((n & 1) == 0) mbar_wait(c.bar + (B_XFULL + n / 2) * 8, 0);
            if ((n & 1) == 0 && warp == 0) TRACEF(270 + n / 2);
            if (n == 0 && warp == 0) TRACE(56);
            mbar_wait(c.bar + (B_RFULL + (n & 3)) * 8, (n >> 2) & 1);
            if (n == 0 && c.w == 0) TRACE(8 + c.par);
            if (n == 1 && warp == 0) TRACE(57);
            if (n == 2 && warp == 0) TRACE(58);
            if (n == 3 && warp == 0) TRACE(59);
            if (warp == 0) TRACEF(64 + n);
            wg_fence();
#pragma unroll
            for (int h = 0; h < 2; h++) {
                const uint32_t alo = c.a_lo + (n >> 1) * 1024 + ((n & 1) * 2 + h) * 2;
                wgmma_n192(q1, alo, HI_128, c.b_lo + lbo(2048) + (n & 3) * 1024 + h * 384, HI_128, (n | h) != 0);
                wgmma_n48(q2, alo, HI_128, c.b_lo + lbo(512) + (n & 3) * 1024 + 768 + h * 96, HI_32, (n | h) != 0);
            }
            wg_commit();
            wg_wait<1>();
            if (n > 0) arrive_both(c, B_REMPTY + ((n - 1) & 3));
        }
        if (c.w == 0) TRACE(10 + c.par);

        float accA[64], accB[64];
        uint32_t qp[20], kp[20], vp[20], hk[10], hv[10], op[20], hp[8];
        const bool first = (tile == 0) && (c.w == 0);
        float2 cs[8];
        f_issue<20>(c, accA);
        f_issue<21>(c, accA);
        f_issue<22>(c, accA);
        {
            mbar_wait(c.bar + B_ST * 8, 0);
            const float2 s0 = lds64(sb + SM_ST + (c.par * 64 + idx0) * 8), s1 = lds64(sb + SM_ST + (c.par * 64 + idx0 + 8) * 8);
            c.r0 = s0.x; c.m0 = s0.y; c.r1 = s1.x; c.m1 = s1.y;
            mbar_wait(c.bar + B_CS * 8, 0);
        }
        const int hdt = (c.w == 3) ? tile + 1 : tile;
        const bool hst = hdt < 16;
        uint8_t* hq_st = (uint8_t*)(g_halo + (size_t)(((hdt * 8 + slot) * 2 + c.par) * 4 + ((c.w + 1) & 3)) * 160 + lane);
        if (RF_ALIGN && (slot & 3) == 3) q_epilogue<true>(c, cs, q1, q2, qp, kp, vp, accA, hst, hq_st);
        else q_epilogue<false>(c, cs, q1, q2, qp, kp, vp, accA, hst, hq_st);
        swiglu_consts(c, c.r0, c.r1);
        if (c.w == 0) TRACE(12 + c.par);

        uint8_t* hdst = nullptr;
        mbar_wait(c.bar + B_CSB * 8, 0);
        swiglu_pre<0, 0, 2>(c, cs); f_issue<30>(c, accB); swiglu_groups<0, 0, 2, 2>(c, accA, cs, hp, hdst);
        swiglu_pre<0, 2, 3>(c, cs); f_issue<31>(c, accB); swiglu_groups<0, 2, 3, 1>(c, accA, cs, hp, hdst);
        hdst = act_piece(c, tile) + (10 + slot) * 16384;
        swiglu_pre<0, 3, 4>(c, cs); f_issue<32>(c, accB); swiglu_groups<0, 3, 4, 1>(c, accA, cs, hp, hdst);
        swiglu_pre<0, 4, 6>(c, cs); f_issue<33>(c, accB); swiglu_groups<0, 4, 6, 2>(c, accA, cs, hp, hdst);
        swiglu_pre<0, 6, 7>(c, cs); f_issue<34>(c, accB); swiglu_groups<0, 6, 7, 1>(c, accA, cs, hp, hdst);
        uint4 t0, t1, t2, t3, t4;
        {
            mbar_wait(c.bar + (B_HALOR + c.par) * 8, 0);
            const uint4* hq = g_halo + (size_t)(((tile * 8 + slot) * 2 + c.par) * 4 + c.w) * 160 + lane;
            t0 = __ldcg(hq); t1 = __ldcg(hq + 32); t2 = __ldcg(hq + 64); t3 = __ldcg(hq + 96); t4 = __ldcg(hq + 128);
        }
        hdst = act_piece(c, tile) + (10 + slot) * 16384;
        swiglu_pre<0, 7, 8>(c, cs); f_issue<35>(c, accB); swiglu_groups<0, 7, 8, 1>(c, accA, cs, hp, hdst);
        arrive_local(c, B_WDONE + 0);
        hk[0] = t0.x; hk[1] = t0.y; hk[3] = t0.z; hk[4] = t0.w; hk[5] = t1.x; hk[6] = t1.y; hk[8] = t1.z; hk[9] = t1.w;
        hk[2] = t2.x; hk[7] = t2.y; hv[0] = t2.z; hv[1] = t2.w; hv[2] = t3.x; hv[3] = t3.y; hv[4] = t3.z; hv[5] = t3.w;
        hv[6] = t4.x; hv[7] = t4.y; hv[8] = t4.z; hv[9] = t4.w;
        float sc[4][4], mx[4][2];
        uint32_t pr[4][4];
        {
            float lg[4][3][4], nq;
            uint32_t qs[4][2];
            attn_prep(c, first, qp, qs, nq);
            f_issue<36>(c, accB);
            block_edge(c);
            attn_logits<0>(qp, qs, kp, hk, nq, lg[0][0], lg[0][1], lg[0][2]); attn_logits<1>(qp, qs, kp, hk, nq, lg[1][0], lg[1][1], lg[1][2]);
            attn_logits<2>(qp, qs, kp, hk, nq, lg[2][0], lg[2][1], lg[2][2]); attn_logits<3>(qp, qs, kp, hk, nq, lg[3][0], lg[3][1], lg[3][2]);
            f_issue<37>(c, accB);
            if (EDGE_AFTER & 1) block_edge(c);
            attn_select(c, lg, sc); attn_max(sc, mx);
        }
        f_issue<38>(c, accB); attn_exp(c, sc, mx);
        f_issue<39>(c, accB); attn_sum(mx);
        if (c.w == 0) TRACE(14 + c.par);

        f_issue<40>(c, accA); attn_probs(c, sc, mx, pr);
        transpose_frags<0, 10>(hv);
        {
            float ov[4][3][4];
            f_issue<41>(c, accA);
            block_edge(c);
            attn_pv<0>(pr[0], vp, hv, ov[0]); attn_pv<1>(pr[1], vp, hv, ov[1]); attn_pv<2>(pr[2], vp, hv, ov[2]); attn_pv<3>(pr[3], vp, hv, ov[3]);
            f_issue<42>(c, accA);
            if (EDGE_AFTER & 2) block_edge(c);
            attn_pack(c, ov, op);
        }
        o_store(c, tile, slot, op);
        f_issue<43>(c, accA);
        arrive_local(c, B_WDONE + 1);
        mbar_wait(c.bar + (B_CSB + 1) * 8, 0);
        {
            const uint32_t sa = launder(sb + SM_ST + (c.par * 64 + idx0) * 8);
            const float2 s0 = lds64(sa), s1 = lds64(sa + 64);
            c.m0 = s0.y; c.m1 = s1.y;
            swiglu_consts(c, s0.x, s1.x);
        }
        swiglu_pre<1, 0, 2>(c, cs); f_issue<44>(c, accA); swiglu_groups<1, 0, 2, 2>(c, accB, cs, hp, nullptr, 0);
        swiglu_pre<1, 2, 4>(c, cs); f_issue<45>(c, accA); swiglu_groups<1, 2, 4, 2>(c, accB, cs, hp, nullptr, own_piece<1>(c));
        swiglu_pre<1, 4, 6>(c, cs); f_issue<46>(c, accA); swiglu_groups<1, 4, 6, 2>(c, accB, cs, hp, nullptr, 0);
        swiglu_pre<1, 6, 7>(c, cs); f_issue<47>(c, accA); swiglu_groups<1, 6, 7, 1>(c, accB, cs, hp, nullptr, 0);
        swiglu_pre<1, 7, 8>(c, cs); f_issue<48>(c, accA); swiglu_groups<1, 7, 8, 1>(c, accB, cs, hp, nullptr, own_piece<1>(c));
        own_done<1>(c);
        f_issue<49>(c, accA);
        if (c.w == 0) TRACE(16 + c.par);

        AccG accG;
        mbar_wait(c.bar + (B_CSB + 2) * 8, 0);
        swiglu_pre<2, 0, 4>(c, cs);
        TP(0);
        wg_wait<0>();
        TP(1);
        arrive_both(c, B_GEMPTY + 3);
        arrive_both(c, B_GEMPTY + 4);
        {
            const uint32_t sdst = own_piece<2>(c);
            swiglu_groups<2, 0, 4, 4>(c, accA, cs, hp, nullptr, sdst);
            swiglu_pre<2, 4, 8>(c, cs);
            swiglu_groups<2, 4, 8, 4>(c, accA, cs, hp, nullptr, sdst);
        }
        TP(2);
        g_issue(c, accG, 0, 0, true, 0);
        TP(3);
        g_issue(c, accG, 1, 0, false, 1);
        TP(4);
        own_done<2>(c);
        TP(5);
        wg_wait<1>(); arrive_both(c, B_GEMPTY + 0);
        g_issue(c, accG, 2, 0, false, 2); wg_wait<1>(); arrive_both(c, B_GEMPTY + 1);
        g_issue(c, accG, 3, 0, false, 3); wg_wait<1>(); arrive_both(c, B_GEMPTY + 2);
        g_issue(c, accG, 4, 0, false, 4); wg_wait<1>(); arrive_both(c, B_GEMPTY + 3);
        g_issue(c, accG, 0, 1, false, 5); wg_wait<1>(); arrive_both(c, B_GEMPTY + 4);
        int gs = 1, gph = 1;
        const int n0 = half ? 8 - NH0 : NH0, nt = 13 + n0;
#pragma unroll 1
        for (int t = 6; t < nt - TAIL_K; t++) {
            g_issue(c, accG, gs, gph, false, t, t == n0 + 9);
            wg_wait<1>();
            if (t + 4 < nt) arrive_both(c, B_GEMPTY + (gs == 0 ? 4 : gs - 1));
            if (++gs == 5) { gs = 0; gph ^= 1; }
        }
        const int R = (lane & 7) + (lane & 8), hi = lane >> 4;
        const int orow = tile * 64 + c.w * 16;
        auto stage_box = [&](int bx, uint32_t dst) {
#pragma unroll
            for (int p = 0; p < 2; p++) {
                const int G = 4 * bx + 2 * p;
                stsm4(dst + R * 64 + ((((G & 3) + hi) ^ ((R >> 1) & 3)) << 4),
                      pack2(accG[4 * G], accG[4 * G + 1]), pack2(accG[4 * G + 2], accG[4 * G + 3]),
                      pack2(accG[4 * G + 4], accG[4 * G + 5]), pack2(accG[4 * G + 6], accG[4 * G + 7]));
            }
        };
        auto out_col = [&](int bx) { return 160 * jj + ((G_ALIGN && (jj & 1)) ? (bx < 4 ? 32 * bx + 32 : 0) : 32 * bx); };
        if (c.w == 0) TRACE(18 + c.par);
        wg_wait<0>();
        {
            if (c.par == 0) bar_sync<1, 128>(); else bar_sync<2, 128>();
            const uint32_t s64 = sb + (c.w >> 1) * 8192 + c.par * 4096 + (c.w & 1) * 2048, s32 = sb + 2 * G_STAGE + c.par * 4096 + c.w * 1024;
            auto stage64 = [&](int bb) {
#pragma unroll
                for (int p = 0; p < 4; p++) {
                    const int G = 8 * bb + 2 * p;
                    stsm4(s64 + bb * G_STAGE + R * 128 + (((2 * p + hi) ^ (R & 7)) << 4),
                          pack2(accG[4 * G], accG[4 * G + 1]), pack2(accG[4 * G + 2], accG[4 * G + 3]),
                          pack2(accG[4 * G + 4], accG[4 * G + 5]), pack2(accG[4 * G + 6], accG[4 * G + 7]));
                }
            };
            stage64(0);
            asm volatile("fence.proxy.async.shared::cta;" ::: "memory");
            __syncwarp();
            if (elect_one()) tma3_red(&maps.o64, s64, out_col(0), orow, c.par);
            stage64(1);
            stage_box(4, s32);
            asm volatile("fence.proxy.async.shared::cta;" ::: "memory");
            __syncwarp();
            if (elect_one()) {
                tma3_red(&maps.o64, s64 + G_STAGE, out_col(2), orow, c.par);
                tma3_red(&maps.o32, s32, out_col(4), orow, c.par);
                asm volatile("cp.async.bulk.commit_group;" ::: "memory");
                asm volatile("cp.async.bulk.wait_group.read 0;" ::: "memory");
            }
        }
        if (c.w == 0) { TRACE(20 + c.par); TRACEG(60 + c.par); }
    }
}

namespace {
typedef CUresult (*EncodeFn)(CUtensorMap*, CUtensorMapDataType, cuuint32_t, void*, const cuuint64_t*, const cuuint64_t*, const cuuint32_t*,
                             const cuuint32_t*, CUtensorMapInterleave, CUtensorMapSwizzle, CUtensorMapL2promotion, CUtensorMapFloatOOBfill);

bool encode(EncodeFn fn, CUtensorMap* m, const void* ptr, int rank, const cuuint64_t* dims, const cuuint64_t* strides, const cuuint32_t* box,
            CUtensorMapSwizzle sw) {
    const cuuint32_t es[5] = {1, 1, 1, 1, 1};
    return fn(m, CU_TENSOR_MAP_DATA_TYPE_BFLOAT16, rank, const_cast<void*>(ptr), dims, strides, box, es, CU_TENSOR_MAP_INTERLEAVE_NONE, sw,
              CU_TENSOR_MAP_L2_PROMOTION_L2_128B, CU_TENSOR_MAP_FLOAT_OOB_FILL_NONE) == CUDA_SUCCESS;
}
}

extern "C" void kernel_launch(void* const* d_in, const int* in_sizes, int n_in, void* d_out, int out_size) {
    (void)in_sizes; (void)n_in; (void)out_size;
    const __nv_bfloat16* x = (const __nv_bfloat16*)d_in[0];
    const __nv_bfloat16* wqkv = (const __nv_bfloat16*)d_in[1];
    const __nv_bfloat16* wo = (const __nv_bfloat16*)d_in[2];
    const __nv_bfloat16* w1 = (const __nv_bfloat16*)d_in[4];
    const __nv_bfloat16* w3 = (const __nv_bfloat16*)d_in[5];
    const __nv_bfloat16* w2 = (const __nv_bfloat16*)d_in[6];

    static EncodeFn fn = nullptr;
    if (!fn) {
        void* p = nullptr;
        cudaDriverEntryPointQueryResult st;
        cudaGetDriverEntryPoint("cuTensorMapEncodeTiled", &p, cudaEnableDefault, &st);
        fn = (EncodeFn)p;
        cudaFuncSetAttribute(fused_block_kernel, cudaFuncAttributeMaxDynamicSharedMemorySize, SM_TOTAL);
    }
    Maps maps;
    {
        const cuuint64_t d[3] = {640, 1024, 2}, s[2] = {2560, 1280};
        const cuuint32_t b[3] = {64, 64, 2};
        encode(fn, &maps.x, x, 3, d, s, b, CU_TENSOR_MAP_SWIZZLE_128B);
    }
    {
        const cuuint64_t d[3] = {640, 640, 3}, s[2] = {3840, 1280};
        const cuuint32_t b[3] = {64, 16, 3}, br[3] = {16, 16, 3};
        encode(fn, &maps.wq, wqkv, 3, d, s, b, CU_TENSOR_MAP_SWIZZLE_128B);
        encode(fn, &maps.wqr, wqkv, 3, d, s, br, CU_TENSOR_MAP_SWIZZLE_32B);
    }
    {
        const cuuint64_t d[2] = {1536, 640}, s[1] = {3072};
        const cuuint32_t b[2] = {64, 64};
        encode(fn, &maps.w1, w1, 2, d, s, b, CU_TENSOR_MAP_SWIZZLE_128B);
        encode(fn, &maps.w3, w3, 2, d, s, b, CU_TENSOR_MAP_SWIZZLE_128B);
    }
    {
        const cuuint64_t d[2] = {1920, 640}, s[1] = {3840};
        const cuuint32_t b[2] = {256, 64};
        encode(fn, &maps.wqc, wqkv, 2, d, s, b, CU_TENSOR_MAP_SWIZZLE_NONE);
    }
    {
        const cuuint64_t d[2] = {1536, 640}, s[1] = {3072};
        const cuuint32_t b[2] = {256, 64};
        encode(fn, &maps.w1c, w1, 2, d, s, b, CU_TENSOR_MAP_SWIZZLE_NONE);
        encode(fn, &maps.w3c, w3, 2, d, s, b, CU_TENSOR_MAP_SWIZZLE_NONE);
    }
    {
        const cuuint64_t do5[5] = {640, 2, 80, 4, 2}, d25[5] = {640, 2, 192, 4, 2}, s5[4] = {1280, 10240, 2560, 128};
        const cuuint32_t b5[5] = {64, 2, 4, 4, 2}, b4[4] = {32, 2, 4, 4};
        encode(fn, &maps.wo2, wo, 5, do5, s5, b5, CU_TENSOR_MAP_SWIZZLE_128B);
        encode(fn, &maps.w22, w2, 5, d25, s5, b5, CU_TENSOR_MAP_SWIZZLE_128B);
        encode(fn, &maps.wo1, wo, 4, do5, s5, b4, CU_TENSOR_MAP_SWIZZLE_128B);
        encode(fn, &maps.w21, w2, 4, d25, s5, b4, CU_TENSOR_MAP_SWIZZLE_128B);
    }
    {
        const cuuint64_t d[3] = {640, 1024, 2}, s[2] = {2560, 1280};
        const cuuint32_t b64[3] = {64, 16, 1}, b32[3] = {32, 16, 1};
        encode(fn, &maps.o64, d_out, 3, d, s, b64, CU_TENSOR_MAP_SWIZZLE_128B);
        encode(fn, &maps.o32, d_out, 3, d, s, b32, CU_TENSOR_MAP_SWIZZLE_64B);
    }
    fused_block_kernel<<<132, 384, SM_TOTAL>>>(maps, x, wqkv, w1, w3, wo, w2, (__nv_bfloat16*)d_out);
}
```

```cpp
#include <cuda_runtime.h>
#include <cuda_bf16.h>
#include <cuda.h>
#include <stdint.h>

namespace {

constexpr int kS = 2048, kD = 640, kF = 1536;

constexpr uint32_t SM_X = 0;
constexpr uint32_t SM_RING = 163840;
constexpr uint32_t SM_OWN = SM_RING + 3 * 16384;
constexpr uint32_t SM_MISC = 229376;
constexpr uint32_t SM_BAR = SM_MISC;
constexpr uint32_t SM_ST = SM_MISC + 448;
constexpr uint32_t SM_CSB0 = SM_ST + 1024;
constexpr uint32_t SM_CS = SM_CSB0 + 512;
constexpr uint32_t SM_TOTAL = 232448;
constexpr uint32_t G_STAGE = 40960;
static_assert(SM_CS + 1024 <= SM_TOTAL, "smem map");
__host__ __device__ constexpr uint32_t sm_csb(int f) { return f == 0 ? SM_CSB0 : SM_CS + (f - 1) * 512; }

#define X_LSU 1
constexpr int B_XFULL = 0;
constexpr int B_RFULL = 10;
constexpr int B_REMPTY = 14;
constexpr int B_GFULL = 18;
constexpr int B_GEMPTY = 23;
constexpr int B_CS = 28;
constexpr int B_ST = 29;
constexpr int B_CSB = 30;
constexpr int B_CSFREE = 33;
constexpr int B_HALOW = 34;
constexpr int B_HALOR = 35;
constexpr int B_WDONE = 37;
constexpr int B_FLAG = 41;
constexpr int B_INIT = 49;
constexpr int B_H1OUT = 50;
constexpr int B_COUNT = 51;
__host__ __device__ constexpr uint32_t bar_count(int i) {
    return (i < B_XFULL + X_LSU) ? 8
         : ((i >= B_REMPTY && i < B_GFULL) || (i >= B_GEMPTY && i < B_CS)) ? 16
         : (i == B_CSFREE) ? 8
         : (i == B_HALOW) ? 2
         : (i == B_HALOR || i == B_HALOR + 1) ? 5
         : (i == B_WDONE + 1) ? 9
         : (i >= B_WDONE && i < B_FLAG) ? 8 : 1;
}

#define INIT_GAP 300
#define POLL_GAP 350
#define G_AUX_GAP 100
#define CS_WAIT 8
#define GATHER_GAP 350
#define NH0 4


__device__ __align__(1024) uint8_t g_act[16 * 34 * 16384];
__device__ __align__(128) unsigned g_csA[4 * 3 * kD];
__device__ __align__(128) unsigned g_csB[2 * 2 * kF];
__device__ __align__(128) unsigned g_stats[kS * 2];
__device__ __align__(128) uint4 g_halo[16 * 8 * 2 * 4 * 5 * 32];
__device__ __align__(128) unsigned g_cntO[16 * 32];
__device__ __align__(128) unsigned g_cntH[16 * 32];
__device__ __align__(128) unsigned g_flagHalo[16 * 8 * 32];
__device__ __align__(128) unsigned g_flagH[2 * 16 * 8 * 32];

struct Maps {
    CUtensorMap x, wq, wqr, w1, w3, wo2, wo1, w22, w21, o64, o32, w1c, w3c, wqc;
};

__device__ __forceinline__ uint32_t smem_u32(const void* p) { return (uint32_t)__cvta_generic_to_shared(p); }
__device__ __forceinline__ uint32_t launder(uint32_t x) { uint32_t y; asm volatile("mov.u32 %0, %1;" : "=r"(y) : "r"(x)); return y; }
template <class T> __device__ __forceinline__ T* launder_ptr(T* p) { T* q; asm volatile("mov.u64 %0, %1;" : "=l"(q) : "l"(p)); return q; }
__device__ __forceinline__ bool elect_one() {
    uint32_t p;
    asm volatile("{\n.reg .pred P;\nelect.sync _|P, 0xffffffff;\nselp.u32 %0,1,0,P;\n}" : "=r"(p));
    return p;
}
__device__ __forceinline__ void mbar_init(uint32_t bar, uint32_t cnt) { asm volatile("mbarrier.init.shared::cta.b64 [%0], %1;" ::"r"(bar), "r"(cnt)); }
__device__ __forceinline__ void mbar_expect_tx(uint32_t bar, uint32_t bytes) {
    asm volatile("mbarrier.arrive.expect_tx.shared::cta.b64 _, [%0], %1;" ::"r"(bar), "r"(bytes) : "memory");
}
__device__ __forceinline__ void mbar_arrive(uint32_t bar) { asm volatile("mbarrier.arrive.shared::cta.b64 _, [%0];" ::"r"(bar) : "memory"); }
__device__ __forceinline__ void mbar_arrive_cluster(uint32_t bar_cluster_addr) {
    asm volatile("mbarrier.arrive.shared::cluster.b64 _, [%0];" ::"r"(bar_cluster_addr) : "memory");
}
__device__ __forceinline__ uint32_t mapa(uint32_t addr, uint32_t cta) {
    uint32_t r; asm("mapa.shared::cluster.u32 %0, %1, %2;" : "=r"(r) : "r"(addr), "r"(cta)); return r;
}
__device__ __forceinline__ bool mbar_try(uint32_t bar, uint32_t parity) {
    uint32_t ok;
    asm volatile("{\n.reg .pred p;\nmbarrier.try_wait.parity.shared::cta.b64 p, [%1], %2;\nselp.u32 %0,1,0,p;\n}"
                 : "=r"(ok) : "r"(bar), "r"(parity) : "memory");
    return ok;
}
__device__ __forceinline__ void mbar_wait(uint32_t bar, uint32_t parity) {
    if (mbar_try(bar, parity)) return;
    int it = 0;
#pragma unroll 1
    while (!mbar_try(bar, parity)) { if (++it > (1 << 17)) break; }
}
__device__ __forceinline__ void tma2(uint32_t dst, const CUtensorMap* m, int c0, int c1, uint32_t bar) {
    asm volatile("cp.async.bulk.tensor.2d.shared::cluster.global.mbarrier::complete_tx::bytes [%0], [%1, {%3, %4}], [%2];"
                 ::"r"(dst), "l"(m), "r"(bar), "r"(c0), "r"(c1) : "memory");
}
__device__ __forceinline__ void tma3(uint32_t dst, const CUtensorMap* m, int c0, int c1, int c2, uint32_t bar) {
    asm volatile("cp.async.bulk.tensor.3d.shared::cluster.global.mbarrier::complete_tx::bytes [%0], [%1, {%3, %4, %5}], [%2];"
                 ::"r"(dst), "l"(m), "r"(bar), "r"(c0), "r"(c1), "r"(c2) : "memory");
}
__device__ __forceinline__ void tma2_mc(uint32_t dst, const CUtensorMap* m, int c0, int c1, uint32_t bar) {
    asm volatile("cp.async.bulk.tensor.2d.shared::cluster.global.mbarrier::complete_tx::bytes.multicast::cluster [%0], [%1, {%3, %4}], [%2], %5;"
                 ::"r"(dst), "l"(m), "r"(bar), "r"(c0), "r"(c1), "h"((uint16_t)3) : "memory");
}
__device__ __forceinline__ void tma3_mc(uint32_t dst, const CUtensorMap* m, int c0, int c1, int c2, uint32_t bar) {
    asm volatile("cp.async.bulk.tensor.3d.shared::cluster.global.mbarrier::complete_tx::bytes.multicast::cluster [%0], [%1, {%3, %4, %5}], [%2], %6;"
                 ::"r"(dst), "l"(m), "r"(bar), "r"(c0), "r"(c1), "r"(c2), "h"((uint16_t)3) : "memory");
}
__device__ __forceinline__ void tma4_mc(uint32_t dst, const CUtensorMap* m, int c0, int c2, uint32_t bar) {
    asm volatile("cp.async.bulk.tensor.4d.shared::cluster.global.mbarrier::complete_tx::bytes.multicast::cluster [%0], [%1, {%3, %5, %4, %5}], [%2], %6;"
                 ::"r"(dst), "l"(m), "r"(bar), "r"(c0), "r"(c2), "r"(0), "h"((uint16_t)3) : "memory");
}
__device__ __forceinline__ void tma5_mc(uint32_t dst, const CUtensorMap* m, int c0, int c2, uint32_t bar) {
    asm volatile("cp.async.bulk.tensor.5d.shared::cluster.global.mbarrier::complete_tx::bytes.multicast::cluster [%0], [%1, {%3, %5, %4, %5, %5}], [%2], %6;"
                 ::"r"(dst), "l"(m), "r"(bar), "r"(c0), "r"(c2), "r"(0), "h"((uint16_t)3) : "memory");
}
__device__ __forceinline__ void bulk_g2s(uint32_t dst, const void* src, uint32_t bytes, uint32_t bar) {
    asm volatile("cp.async.bulk.shared::cluster.global.mbarrier::complete_tx::bytes [%0], [%1], %2, [%3];"
                 ::"r"(dst), "l"(src), "r"(bytes), "r"(bar) : "memory");
}
__device__ __forceinline__ uint4 lds128(uint32_t a) {
    uint4 v; asm volatile("ld.shared.v4.u32 {%0,%1,%2,%3}, [%4];" : "=r"(v.x), "=r"(v.y), "=r"(v.z), "=r"(v.w) : "r"(a) : "memory"); return v;
}
__device__ __forceinline__ void sts128(uint32_t a, uint4 v) {
    asm volatile("st.shared.v4.u32 [%0], {%1,%2,%3,%4};" ::"r"(a), "r"(v.x), "r"(v.y), "r"(v.z), "r"(v.w) : "memory");
}
__device__ __forceinline__ void wg_fence() { asm volatile("wgmma.fence.sync.aligned;" ::: "memory"); }
__device__ __forceinline__ void wg_commit() { asm volatile("wgmma.commit_group.sync.aligned;" ::: "memory"); }
template <int N> __device__ __forceinline__ void wg_wait() { asm volatile("wgmma.wait_group.sync.aligned %0;" ::"n"(N) : "memory"); }
__device__ __forceinline__ unsigned ld_acquire(const unsigned* p) {
    unsigned v; asm volatile("ld.acquire.gpu.global.u32 %0, [%1];" : "=r"(v) : "l"(p) : "memory"); return v;
}
__device__ __forceinline__ void fence_gpu() { asm volatile("fence.acq_rel.gpu;" ::: "memory"); }
__device__ __forceinline__ void fence_async_global() { asm volatile("fence.proxy.async.global;" ::: "memory"); }
__device__ __forceinline__ void red_add(unsigned* p, unsigned v) { asm volatile("red.relaxed.gpu.global.add.u32 [%0], %1;" ::"l"(p), "r"(v) : "memory"); }
__device__ __forceinline__ void st_relaxed(unsigned* p, unsigned v) { asm volatile("st.relaxed.gpu.global.u32 [%0], %1;" ::"l"(p), "r"(v) : "memory"); }
__device__ __forceinline__ unsigned ld_relaxed(const unsigned* p) {
    unsigned v; asm volatile("ld.relaxed.gpu.global.u32 %0, [%1];" : "=r"(v) : "l"(p) : "memory"); return v;
}
__device__ __forceinline__ unsigned tagged(unsigned tag, float v) { return ((__float_as_uint(v) + 8u) & ~15u) | (tag & 15u); }
__device__ __forceinline__ bool tag_ok(const uint4& v, unsigned tag) { return (((v.x ^ tag) | (v.y ^ tag) | (v.z ^ tag) | (v.w ^ tag)) & 15u) == 0; }
__device__ __forceinline__ float tag_val(unsigned v) { return __uint_as_float(v & ~15u); }
__device__ __forceinline__ void st_tag2(unsigned* p, unsigned a, unsigned b) {
    asm volatile("st.relaxed.gpu.global.v2.u32 [%0], {%1, %2};" ::"l"(p), "r"(a), "r"(b) : "memory");
}
__device__ __forceinline__ uint4 ld_tag4(const unsigned* p) {
    uint4 v; asm volatile("ld.relaxed.gpu.global.v4.u32 {%0,%1,%2,%3}, [%4];" : "=r"(v.x), "=r"(v.y), "=r"(v.z), "=r"(v.w) : "l"(p) : "memory"); return v;
}
__device__ __forceinline__ void poll_ge(const unsigned* p, unsigned target) {
    int it = 0;
#pragma unroll 1
    while ((int)(ld_acquire(p) - target) < 0) { if (++it > (1 << 16)) break; }
}
__device__ __forceinline__ void spin(int cycles) { const long long t0 = clock64(); while (clock64() - t0 < cycles) { } }
__device__ __forceinline__ void gather2(const unsigned* p0, const unsigned* p1, unsigned tag, uint4& r0, uint4& r1) {
    uint4 a0 = ld_tag4(p0), a1 = ld_tag4(p1);
    spin(GATHER_GAP);
    uint4 b0 = ld_tag4(p0), b1 = ld_tag4(p1);
    spin(GATHER_GAP);
    uint4 c0 = ld_tag4(p0), c1 = ld_tag4(p1);
#pragma unroll 1
    for (int it = 0; it < (1 << 14); it++) {
        if (__all_sync(0xffffffffu, tag_ok(a0, tag) && tag_ok(a1, tag))) { r0 = a0; r1 = a1; return; }
        a0 = ld_tag4(p0); a1 = ld_tag4(p1);
        if (__all_sync(0xffffffffu, tag_ok(b0, tag) && tag_ok(b1, tag))) { r0 = b0; r1 = b1; return; }
        b0 = ld_tag4(p0); b1 = ld_tag4(p1);
        if (__all_sync(0xffffffffu, tag_ok(c0, tag) && tag_ok(c1, tag))) { r0 = c0; r1 = c1; return; }
        c0 = ld_tag4(p0); c1 = ld_tag4(p1);
    }
    r0 = a0; r1 = a1;
}
__device__ __forceinline__ void poll_multi(const unsigned* p, unsigned target, uint32_t bar, bool active) {
    bool done = !active;
    unsigned v0 = 0, v1 = 0, v2 = 0;
    if (!done) v0 = ld_relaxed(p);
    spin(POLL_GAP);
    if (!done) v1 = ld_relaxed(p);
    spin(POLL_GAP);
    if (!done) v2 = ld_relaxed(p);
#pragma unroll 1
    for (int it = 0; it < (1 << 15); it++) {
        if (!done && (int)(v0 - target) >= 0) { fence_async_global(); mbar_arrive(bar); done = true; }
        if (__all_sync(0xffffffffu, done)) return;
        if (!done) v0 = ld_relaxed(p);
        if (!done && (int)(v1 - target) >= 0) { fence_async_global(); mbar_arrive(bar); done = true; }
        if (__all_sync(0xffffffffu, done)) return;
        if (!done) v1 = ld_relaxed(p);
        if (!done && (int)(v2 - target) >= 0) { fence_async_global(); mbar_arrive(bar); done = true; }
        if (__all_sync(0xffffffffu, done)) return;
        if (!done) v2 = ld_relaxed(p);
    }
    if (!done) mbar_arrive(bar);
}
template <int ID, int N> __device__ __forceinline__ void bar_sync() { asm volatile("bar.sync %0, %1;" ::"n"(ID), "n"(N) : "memory"); }
__device__ __forceinline__ float ex2(float x) { float y; asm("ex2.approx.ftz.f32 %0, %1;" : "=f"(y) : "f"(x)); return y; }
__device__ __forceinline__ float rcp(float x) { float y; asm("rcp.approx.ftz.f32 %0, %1;" : "=f"(y) : "f"(x)); return y; }
__device__ __forceinline__ float tanh_fast(float x) { float y; asm("tanh.approx.f32 %0, %1;" : "=f"(y) : "f"(x)); return y; }
__device__ __forceinline__ uint32_t pack2(float lo, float hi) {
    uint32_t r; asm("cvt.rn.bf16x2.f32 %0, %1, %2;" : "=r"(r) : "f"(hi), "f"(lo)); return r;
}
__device__ __forceinline__ float bf_lo(uint32_t v) { return __uint_as_float(v << 16); }
__device__ __forceinline__ float bf_hi(uint32_t v) { return __uint_as_float(v & 0xffff0000u); }
__device__ __forceinline__ float2 lds64(uint32_t a) { float2 v; asm volatile("ld.shared.v2.f32 {%0,%1}, [%2];" : "=f"(v.x), "=f"(v.y) : "r"(a)); return v; }
__device__ __forceinline__ void mma16v(float (&d)[4], uint32_t a0, uint32_t a1, uint32_t a2, uint32_t a3, uint32_t b0, uint32_t b1,
                                       float c0, float c1, float c2, float c3) {
    asm volatile("mma.sync.aligned.m16n8k16.row.col.f32.bf16.bf16.f32 {%0,%1,%2,%3}, {%4,%5,%6,%7}, {%8,%9}, {%10,%11,%12,%13};"
        : "=f"(d[0]), "=f"(d[1]), "=f"(d[2]), "=f"(d[3]) : "r"(a0), "r"(a1), "r"(a2), "r"(a3), "r"(b0), "r"(b1), "f"(c0), "f"(c1), "f"(c2), "f"(c3));
}
__device__ __forceinline__ void mma8v(float (&c)[4], uint32_t a0, uint32_t a1, uint32_t b0) {
    asm volatile("mma.sync.aligned.m16n8k8.row.col.f32.bf16.bf16.f32 {%0,%1,%2,%3}, {%4,%5}, {%6}, {%0,%1,%2,%3};"
        : "+f"(c[0]), "+f"(c[1]), "+f"(c[2]), "+f"(c[3]) : "r"(a0), "r"(a1), "r"(b0));
}
__device__ __forceinline__ uint32_t pack2v(float lo, float hi) {
    uint32_t r; asm volatile("cvt.rn.bf16x2.f32 %0, %1, %2;" : "=r"(r) : "f"(hi), "f"(lo)); return r;
}
__device__ __forceinline__ uint32_t andv(uint32_t a, uint32_t b) {
    uint32_t r; asm volatile("and.b32 %0, %1, %2;" : "=r"(r) : "r"(a), "r"(b)); return r;
}
__device__ __forceinline__ uint32_t movv(uint32_t a) {
    uint32_t r; asm volatile("mov.b32 %0, %1;" : "=r"(r) : "r"(a)); return r;
}
__device__ __forceinline__ uint32_t movm(uint32_t a) {
    uint32_t d; asm volatile("movmatrix.sync.aligned.m8n8.trans.b16 %0, %1;" : "=r"(d) : "r"(a)); return d;
}

__device__ __forceinline__ void wgmma_n48(float (&d)[24], uint32_t alo, uint32_t ahi, uint32_t blo, uint32_t bhi, int sd) {
    asm volatile("{\n.reg .pred p;\n.reg .b64 da, db;\nsetp.ne.b32 p, %28, 0;\nmov.b64 da, {%24,%25};\nmov.b64 db, {%26,%27};\n"
        "wgmma.mma_async.sync.aligned.m64n48k16.f32.bf16.bf16 {"
        "%0,%1,%2,%3,%4,%5,%6,%7,%8,%9,%10,%11,%12,%13,%14,%15,"
        "%16,%17,%18,%19,%20,%21,%22,%23"
        "}, da, db, p, 1, 1, 0, 1;\n}\n"
        : "+f"(d[0]), "+f"(d[1]), "+f"(d[2]), "+f"(d[3]), "+f"(d[4]), "+f"(d[5]), "+f"(d[6]), "+f"(d[7]),
          "+f"(d[8]), "+f"(d[9]), "+f"(d[10]), "+f"(d[11]), "+f"(d[12]), "+f"(d[13]), "+f"(d[14]), "+f"(d[15]),
          "+f"(d[16]), "+f"(d[17]), "+f"(d[18]), "+f"(d[19]), "+f"(d[20]), "+f"(d[21]), "+f"(d[22]), "+f"(d[23])
        : "r"(alo), "r"(ahi), "r"(blo), "r"(bhi), "r"(sd));
}
__device__ __forceinline__ void wgmma_n128(float (&d)[64], uint32_t alo, uint32_t ahi, uint32_t blo, uint32_t bhi, int sd) {
    asm volatile("{\n.reg .pred p;\n.reg .b64 da, db;\nsetp.ne.b32 p, %68, 0;\nmov.b64 da, {%64,%65};\nmov.b64 db, {%66,%67};\n"
        "wgmma.mma_async.sync.aligned.m64n128k16.f32.bf16.bf16 {"
        "%0,%1,%2,%3,%4,%5,%6,%7,%8,%9,%10,%11,%12,%13,%14,%15,"
        "%16,%17,%18,%19,%20,%21,%22,%23,%24,%25,%26,%27,%28,%29,%30,%31,"
        "%32,%33,%34,%35,%36,%37,%38,%39,%40,%41,%42,%43,%44,%45,%46,%47,"
        "%48,%49,%50,%51,%52,%53,%54,%55,%56,%57,%58,%59,%60,%61,%62,%63"
        "}, da, db, p, 1, 1, 0, 1;\n}\n"
        : "+f"(d[0]), "+f"(d[1]), "+f"(d[2]), "+f"(d[3]), "+f"(d[4]), "+f"(d[5]), "+f"(d[6]), "+f"(d[7]),
          "+f"(d[8]), "+f"(d[9]), "+f"(d[10]), "+f"(d[11]), "+f"(d[12]), "+f"(d[13]), "+f"(d[14]), "+f"(d[15]),
          "+f"(d[16]), "+f"(d[17]), "+f"(d[18]), "+f"(d[19]), "+f"(d[20]), "+f"(d[21]), "+f"(d[22]), "+f"(d[23]),
          "+f"(d[24]), "+f"(d[25]), "+f"(d[26]), "+f"(d[27]), "+f"(d[28]), "+f"(d[29]), "+f"(d[30]), "+f"(d[31]),
          "+f"(d[32]), "+f"(d[33]), "+f"(d[34]), "+f"(d[35]), "+f"(d[36]), "+f"(d[37]), "+f"(d[38]), "+f"(d[39]),
          "+f"(d[40]), "+f"(d[41]), "+f"(d[42]), "+f"(d[43]), "+f"(d[44]), "+f"(d[45]), "+f"(d[46]), "+f"(d[47]),
          "+f"(d[48]), "+f"(d[49]), "+f"(d[50]), "+f"(d[51]), "+f"(d[52]), "+f"(d[53]), "+f"(d[54]), "+f"(d[55]),
          "+f"(d[56]), "+f"(d[57]), "+f"(d[58]), "+f"(d[59]), "+f"(d[60]), "+f"(d[61]), "+f"(d[62]), "+f"(d[63])
        : "r"(alo), "r"(ahi), "r"(blo), "r"(bhi), "r"(sd));
}
__device__ __forceinline__ void wgmma_n160(float (&d)[80], uint32_t alo, uint32_t ahi, uint32_t blo, uint32_t bhi, int sd) {
    asm volatile("{\n.reg .pred p;\n.reg .b64 da, db;\nsetp.ne.b32 p, %84, 0;\nmov.b64 da, {%80,%81};\nmov.b64 db, {%82,%83};\n"
        "wgmma.mma_async.sync.aligned.m64n160k16.f32.bf16.bf16 {"
        "%0,%1,%2,%3,%4,%5,%6,%7,%8,%9,%10,%11,%12,%13,%14,%15,"
        "%16,%17,%18,%19,%20,%21,%22,%23,%24,%25,%26,%27,%28,%29,%30,%31,"
        "%32,%33,%34,%35,%36,%37,%38,%39,%40,%41,%42,%43,%44,%45,%46,%47,"
        "%48,%49,%50,%51,%52,%53,%54,%55,%56,%57,%58,%59,%60,%61,%62,%63,"
        "%64,%65,%66,%67,%68,%69,%70,%71,%72,%73,%74,%75,%76,%77,%78,%79"
        "}, da, db, p, 1, 1, 0, 1;\n}\n"
        : "+f"(d[0]), "+f"(d[1]), "+f"(d[2]), "+f"(d[3]), "+f"(d[4]), "+f"(d[5]), "+f"(d[6]), "+f"(d[7]),
          "+f"(d[8]), "+f"(d[9]), "+f"(d[10]), "+f"(d[11]), "+f"(d[12]), "+f"(d[13]), "+f"(d[14]), "+f"(d[15]),
          "+f"(d[16]), "+f"(d[17]), "+f"(d[18]), "+f"(d[19]), "+f"(d[20]), "+f"(d[21]), "+f"(d[22]), "+f"(d[23]),
          "+f"(d[24]), "+f"(d[25]), "+f"(d[26]), "+f"(d[27]), "+f"(d[28]), "+f"(d[29]), "+f"(d[30]), "+f"(d[31]),
          "+f"(d[32]), "+f"(d[33]), "+f"(d[34]), "+f"(d[35]), "+f"(d[36]), "+f"(d[37]), "+f"(d[38]), "+f"(d[39]),
          "+f"(d[40]), "+f"(d[41]), "+f"(d[42]), "+f"(d[43]), "+f"(d[44]), "+f"(d[45]), "+f"(d[46]), "+f"(d[47]),
          "+f"(d[48]), "+f"(d[49]), "+f"(d[50]), "+f"(d[51]), "+f"(d[52]), "+f"(d[53]), "+f"(d[54]), "+f"(d[55]),
          "+f"(d[56]), "+f"(d[57]), "+f"(d[58]), "+f"(d[59]), "+f"(d[60]), "+f"(d[61]), "+f"(d[62]), "+f"(d[63]),
          "+f"(d[64]), "+f"(d[65]), "+f"(d[66]), "+f"(d[67]), "+f"(d[68]), "+f"(d[69]), "+f"(d[70]), "+f"(d[71]),
          "+f"(d[72]), "+f"(d[73]), "+f"(d[74]), "+f"(d[75]), "+f"(d[76]), "+f"(d[77]), "+f"(d[78]), "+f"(d[79])
        : "r"(alo), "r"(ahi), "r"(blo), "r"(bhi), "r"(sd));
}
__device__ __forceinline__ void wgmma_n192(float (&d)[96], uint32_t alo, uint32_t ahi, uint32_t blo, uint32_t bhi, int sd) {
    asm volatile("{\n.reg .pred p;\n.reg .b64 da, db;\nsetp.ne.b32 p, %100, 0;\nmov.b64 da, {%96,%97};\nmov.b64 db, {%98,%99};\n"
        "wgmma.mma_async.sync.aligned.m64n192k16.f32.bf16.bf16 {"
        "%0,%1,%2,%3,%4,%5,%6,%7,%8,%9,%10,%11,%12,%13,%14,%15,"
        "%16,%17,%18,%19,%20,%21,%22,%23,%24,%25,%26,%27,%28,%29,%30,%31,"
        "%32,%33,%34,%35,%36,%37,%38,%39,%40,%41,%42,%43,%44,%45,%46,%47,"
        "%48,%49,%50,%51,%52,%53,%54,%55,%56,%57,%58,%59,%60,%61,%62,%63,"
        "%64,%65,%66,%67,%68,%69,%70,%71,%72,%73,%74,%75,%76,%77,%78,%79,"
        "%80,%81,%82,%83,%84,%85,%86,%87,%88,%89,%90,%91,%92,%93,%94,%95"
        "}, da, db, p, 1, 1, 0, 1;\n}\n"
        : "+f"(d[0]), "+f"(d[1]), "+f"(d[2]), "+f"(d[3]), "+f"(d[4]), "+f"(d[5]), "+f"(d[6]), "+f"(d[7]),
          "+f"(d[8]), "+f"(d[9]), "+f"(d[10]), "+f"(d[11]), "+f"(d[12]), "+f"(d[13]), "+f"(d[14]), "+f"(d[15]),
          "+f"(d[16]), "+f"(d[17]), "+f"(d[18]), "+f"(d[19]), "+f"(d[20]), "+f"(d[21]), "+f"(d[22]), "+f"(d[23]),
          "+f"(d[24]), "+f"(d[25]), "+f"(d[26]), "+f"(d[27]), "+f"(d[28]), "+f"(d[29]), "+f"(d[30]), "+f"(d[31]),
          "+f"(d[32]), "+f"(d[33]), "+f"(d[34]), "+f"(d[35]), "+f"(d[36]), "+f"(d[37]), "+f"(d[38]), "+f"(d[39]),
          "+f"(d[40]), "+f"(d[41]), "+f"(d[42]), "+f"(d[43]), "+f"(d[44]), "+f"(d[45]), "+f"(d[46]), "+f"(d[47]),
          "+f"(d[48]), "+f"(d[49]), "+f"(d[50]), "+f"(d[51]), "+f"(d[52]), "+f"(d[53]), "+f"(d[54]), "+f"(d[55]),
          "+f"(d[56]), "+f"(d[57]), "+f"(d[58]), "+f"(d[59]), "+f"(d[60]), "+f"(d[61]), "+f"(d[62]), "+f"(d[63]),
          "+f"(d[64]), "+f"(d[65]), "+f"(d[66]), "+f"(d[67]), "+f"(d[68]), "+f"(d[69]), "+f"(d[70]), "+f"(d[71]),
          "+f"(d[72]), "+f"(d[73]), "+f"(d[74]), "+f"(d[75]), "+f"(d[76]), "+f"(d[77]), "+f"(d[78]), "+f"(d[79]),
          "+f"(d[80]), "+f"(d[81]), "+f"(d[82]), "+f"(d[83]), "+f"(d[84]), "+f"(d[85]), "+f"(d[86]), "+f"(d[87]),
          "+f"(d[88]), "+f"(d[89]), "+f"(d[90]), "+f"(d[91]), "+f"(d[92]), "+f"(d[93]), "+f"(d[94]), "+f"(d[95])
        : "r"(alo), "r"(ahi), "r"(blo), "r"(bhi), "r"(sd));
}


constexpr uint32_t HI_128 = 0x40000040u;
constexpr uint32_t HI_64 = 0x80000020u;
constexpr uint32_t HI_32 = 0xC0000010u;
__device__ __forceinline__ constexpr uint32_t lbo(uint32_t bytes) { return (bytes >> 4) << 16; }

struct Ctx {
    uint32_t sb;
    uint32_t bar;
    uint32_t rbar;
    uint32_t a_lo;
    uint32_t b_lo;
    int lane, q, g, w, par;
    uint32_t aoff;
    float m0, m1, r0, r1;
    float ga0, ga1, gb0, gb1;
};

__device__ __forceinline__ void arrive_both(const Ctx& c, int bar_idx) {
    if (c.lane < 2) mbar_arrive_cluster(c.rbar + bar_idx * 8);
}
__device__ __forceinline__ void arrive_local(const Ctx& c, int bar_idx) {
    __syncwarp();
    if (c.lane == 0) mbar_arrive(c.bar + bar_idx * 8);
}

__device__ __forceinline__ void stsm4(uint32_t addr, uint32_t a, uint32_t b, uint32_t c, uint32_t d) {
    asm volatile("stmatrix.sync.aligned.m8n8.x4.shared.b16 [%0], {%1, %2, %3, %4};" ::"r"(addr), "r"(a), "r"(b), "r"(c), "r"(d) : "memory");
}
__device__ __forceinline__ void tma3_store(const CUtensorMap* m, uint32_t src, int c0, int c1, int c2) {
    asm volatile("cp.async.bulk.tensor.3d.global.shared::cta.tile.bulk_group [%0, {%2, %3, %4}], [%1];"
                 ::"l"(m), "r"(src), "r"(c0), "r"(c1), "r"(c2) : "memory");
}
__device__ __forceinline__ void tma3_red(const CUtensorMap* m, uint32_t src, int c0, int c1, int c2) {
    asm volatile("cp.reduce.async.bulk.tensor.3d.global.shared::cta.add.tile.bulk_group [%0, {%2, %3, %4}], [%1];"
                 ::"l"(m), "r"(src), "r"(c0), "r"(c1), "r"(c2) : "memory");
}

template <bool SCALE>
__device__ __forceinline__ void ln_pack(const Ctx& c, const float* a, const float2 cs, uint32_t& lo, uint32_t& hi) {
    if (SCALE) {
        lo = pack2(fmaf(c.m0, cs.x, a[0]) * c.r0, fmaf(c.m0, cs.y, a[1]) * c.r0);
        hi = pack2(fmaf(c.m1, cs.x, a[2]) * c.r1, fmaf(c.m1, cs.y, a[3]) * c.r1);
    } else {
        lo = pack2(fmaf(c.m0, cs.x, a[0]), fmaf(c.m0, cs.y, a[1]));
        hi = pack2(fmaf(c.m1, cs.x, a[2]), fmaf(c.m1, cs.y, a[3]));
    }
}
__host__ __device__ constexpr int qg_part(int i) { return i < 10 ? 1 : i < 20 ? 2 : 0; }
template <bool RF> __host__ __device__ constexpr int qg_main(int G) { return RF ? (G < 2 ? -1 - G : G - 2) : (G < 8 ? G : -1 - (G - 8)); }
template <bool RF> __host__ __device__ constexpr int qg_col(int i) {
    return qg_main<RF>(i % 10) >= 0 ? qg_part(i) * 64 + qg_main<RF>(i % 10) * 8 : 192 + qg_part(i) * 16 + (-1 - qg_main<RF>(i % 10)) * 8;
}
template <bool RF, int I0, int I1>
__device__ __forceinline__ void qkv_pre(const Ctx& c, float2 (&cs)[8]) {
#pragma unroll
    for (int i = I0; i < I1; i++) cs[i - I0] = lds64(c.sb + SM_CS + (qg_col<RF>(i) + 2 * c.q) * 4);
}
template <bool RF, int I0, int I1>
__device__ __forceinline__ void qkv_pack(const Ctx& c, const float2 (&cs)[8], const float (&a1)[96], const float (&a2)[24],
                                         uint32_t (&qp)[20], uint32_t (&kp)[20], uint32_t (&vp)[20]) {
#pragma unroll
    for (int i = I0; i < I1; i++) {
        const int P = qg_part(i), G = i % 10, M = qg_main<RF>(G);
        const float* a = (M >= 0) ? &a1[P * 32 + M * 4] : &a2[P * 8 + (-1 - M) * 4];
        if (P == 0) ln_pack<false>(c, a, cs[i - I0], qp[2 * G], qp[2 * G + 1]);
        else if (P == 1) ln_pack<true>(c, a, cs[i - I0], kp[2 * G], kp[2 * G + 1]);
        else ln_pack<true>(c, a, cs[i - I0], vp[2 * G], vp[2 * G + 1]);
    }
}

__device__ __forceinline__ void attn_prep(const Ctx& c, bool first, const uint32_t (&qp)[20], uint32_t (&qs)[4][2], float& nq) {
    const uint32_t lo = (c.q < 2) ? 0xffffffffu : 0u, hi = ~lo;
#pragma unroll
    for (int h = 0; h < 4; h++) {
        const int GS = (h < 2) ? 2 : 7;
        qs[h][0] = andv(qp[2 * GS], (h & 1) ? hi : lo);
        qs[h][1] = andv(qp[2 * GS + 1], (h & 1) ? hi : lo);
    }
    nq = __uint_as_float(movv(first ? 0xff800000u : 0u));
}
template <int H>
__device__ __forceinline__ void attn_logits(const uint32_t (&qp)[20], const uint32_t (&qs)[4][2], const uint32_t (&kp)[20],
                                            const uint32_t (&hk)[10], float nq, float (&sP)[4], float (&sL)[4], float (&sU)[4]) {
    constexpr int GA = (H == 0) ? 0 : (H == 1) ? 3 : (H == 2) ? 5 : 8;
    constexpr int GS = (H < 2) ? 2 : 7;
    mma16v(sP, qp[2 * GA], qp[2 * GA + 1], qp[2 * GA + 2], qp[2 * GA + 3], hk[GA], hk[GA + 1], nq, nq, nq, nq);
    mma16v(sL, qp[2 * GA], qp[2 * GA + 1], qp[2 * GA + 2], qp[2 * GA + 3], kp[2 * GA], kp[2 * GA + 2], 0.f, 0.f, 0.f, 0.f);
    mma16v(sU, qp[2 * GA], qp[2 * GA + 1], qp[2 * GA + 2], qp[2 * GA + 3], kp[2 * GA + 1], kp[2 * GA + 3], 0.f, 0.f, 0.f, 0.f);
    mma8v(sP, qs[H][0], qs[H][1], hk[GS]);
    mma8v(sL, qs[H][0], qs[H][1], kp[2 * GS]);
    mma8v(sU, qs[H][0], qs[H][1], kp[2 * GS + 1]);
}
__device__ __forceinline__ void attn_select(const Ctx& c, const float (&lg)[4][3][4], float (&s)[4][4]) {
    const bool gt0 = 2 * c.q > c.g, gt1 = 2 * c.q + 1 > c.g;
#pragma unroll
    for (int h = 0; h < 4; h++) {
        s[h][0] = gt0 ? lg[h][0][0] : lg[h][1][0];
        s[h][1] = gt1 ? lg[h][0][1] : lg[h][1][1];
        s[h][2] = gt0 ? lg[h][1][2] : lg[h][2][2];
        s[h][3] = gt1 ? lg[h][1][3] : lg[h][2][3];
    }
}
constexpr float kScale = 0.22360679774997896f * 1.4426950408889634f;
__device__ __forceinline__ void attn_max(const float (&s)[4][4], float (&m)[4][2]) {
#pragma unroll
    for (int h = 0; h < 4; h++) { m[h][0] = fmaxf(s[h][0], s[h][1]); m[h][1] = fmaxf(s[h][2], s[h][3]); }
#pragma unroll
    for (int o = 1; o < 4; o <<= 1) {
#pragma unroll
        for (int h = 0; h < 4; h++) {
            m[h][0] = fmaxf(m[h][0], __shfl_xor_sync(0xffffffffu, m[h][0], o));
            m[h][1] = fmaxf(m[h][1], __shfl_xor_sync(0xffffffffu, m[h][1], o));
        }
    }
}
__device__ __forceinline__ void attn_exp(const Ctx& c, float (&s)[4][4], float (&m)[4][2]) {
    constexpr float kf = 2.f * kScale;
    const float k0 = kf * c.ga0, k1 = kf * c.ga1;
#pragma unroll
    for (int h = 0; h < 4; h++) {
        const float m0 = m[h][0] * -k0, m1 = m[h][1] * -k1;
        s[h][0] = ex2(fmaf(s[h][0], k0, m0)); s[h][1] = ex2(fmaf(s[h][1], k0, m0));
        s[h][2] = ex2(fmaf(s[h][2], k1, m1)); s[h][3] = ex2(fmaf(s[h][3], k1, m1));
        m[h][0] = s[h][0] + s[h][1]; m[h][1] = s[h][2] + s[h][3];
    }
}
__device__ __forceinline__ void attn_sum(float (&m)[4][2]) {
#pragma unroll
    for (int o = 1; o < 4; o <<= 1) {
#pragma unroll
        for (int h = 0; h < 4; h++) {
            m[h][0] += __shfl_xor_sync(0xffffffffu, m[h][0], o);
            m[h][1] += __shfl_xor_sync(0xffffffffu, m[h][1], o);
        }
    }
#pragma unroll
    for (int h = 0; h < 4; h++) { m[h][0] = rcp(m[h][0]); m[h][1] = rcp(m[h][1]); }
}
__device__ __forceinline__ void attn_probs(const Ctx& c, const float (&s)[4][4], const float (&m)[4][2], uint32_t (&p)[4][4]) {
    const uint32_t mk = ((2 * c.q > c.g) ? 0x0000ffffu : 0u) | ((2 * c.q + 1 > c.g) ? 0xffff0000u : 0u);
#pragma unroll
    for (int h = 0; h < 4; h++) {
        const uint32_t lo = pack2(s[h][0] * m[h][0], s[h][1] * m[h][0]), hi = pack2(s[h][2] * m[h][1], s[h][3] * m[h][1]);
        p[h][0] = andv(lo, mk); p[h][1] = andv(lo, ~mk); p[h][2] = andv(hi, mk); p[h][3] = andv(hi, ~mk);
    }
}
template <int I0, int I1, int N>
__device__ __forceinline__ void transpose_frags(uint32_t (&v)[N]) {
#pragma unroll
    for (int i = I0; i < I1; i++) v[i] = movm(v[i]);
}
template <int H>
__device__ __forceinline__ void attn_pv(const uint32_t (&p)[4], const uint32_t (&vp)[20], const uint32_t (&hv)[10], float (&o)[3][4]) {
    constexpr int GA = (H == 0) ? 0 : (H == 1) ? 3 : (H == 2) ? 5 : 8;
    constexpr int GS = (H < 2) ? 2 : 7;
#pragma unroll
    for (int t = 0; t < 3; t++) {
        const int G = (t < 2) ? GA + t : GS;
        mma16v(o[t], p[0], 0u, p[1], p[2], hv[G], vp[2 * G], 0.f, 0.f, 0.f, 0.f);
        mma8v(o[t], 0u, p[3], vp[2 * G + 1]);
    }
}
__device__ __forceinline__ void attn_pack(const Ctx& c, const float (&o)[4][3][4], uint32_t (&op)[20]) {
#pragma unroll
    for (int h = 0; h < 4; h++) {
        const int GA = (h == 0) ? 0 : (h == 1) ? 3 : (h == 2) ? 5 : 8;
#pragma unroll
        for (int t = 0; t < 2; t++) { op[2 * (GA + t)] = pack2v(o[h][t][0], o[h][t][1]); op[2 * (GA + t) + 1] = pack2v(o[h][t][2], o[h][t][3]); }
    }
    const bool even = c.q < 2;
#pragma unroll
    for (int hp = 0; hp < 2; hp++) {
        const int GS = hp ? 7 : 2;
        const float* e = o[2 * hp][2];
        const float* d = o[2 * hp + 1][2];
        op[2 * GS] = pack2v(even ? e[0] : d[0], even ? e[1] : d[1]);
        op[2 * GS + 1] = pack2v(even ? e[2] : d[2], even ? e[3] : d[3]);
    }
}

__device__ __forceinline__ void swiglu_consts(Ctx& c, float r0, float r1) {
    c.ga0 = 0.5f * r0; c.ga1 = 0.5f * r1; c.gb0 = c.ga0 * r0; c.gb1 = c.ga1 * r1;
}
__device__ __forceinline__ uint32_t piece_off() {
    const uint32_t t = launder(threadIdx.x);
    const uint32_t row = (t >> 7) * 64 + ((t >> 5) & 3) * 16 + ((t & 31) >> 2);
    return row * 64 + (((t & 3) ^ ((row >> 1) & 3)) << 4);
}
__device__ __forceinline__ uint8_t* act_piece(const Ctx& c, int tile) { return g_act + (size_t)tile * (34 * 16384) + c.aoff; }
__device__ __forceinline__ void stg128(uint8_t* p, uint32_t a, uint32_t b, uint32_t c, uint32_t d) {
    asm volatile("st.global.v4.b32 [%0], {%1, %2, %3, %4};" ::"l"(p), "r"(a), "r"(b), "r"(c), "r"(d) : "memory");
}
__device__ __forceinline__ void stg64(uint8_t* p, uint32_t a, uint32_t b) {
    asm volatile("st.global.v2.b32 [%0], {%1, %2};" ::"l"(p), "r"(a), "r"(b) : "memory");
}

__device__ __forceinline__ void o_store(const Ctx& c, int tile, int slot, const uint32_t (&op)[20]) {
    uint8_t* odst = act_piece(c, tile) + 5 * (slot >> 1) * 8192;
    if ((slot & 1) == 0) {
        stg128(odst, op[0], op[2], op[4], op[6]);
        stg128(odst + 512, op[1], op[3], op[5], op[7]);
        stg128(odst + 8192, op[8], op[10], op[12], op[14]);
        stg128(odst + 8192 + 512, op[9], op[11], op[13], op[15]);
        stg64(odst + 16384, op[16], op[18]);
        stg64(odst + 16384 + 512, op[17], op[19]);
    } else {
        stg64(odst + 16384 + 8, op[0], op[2]);
        stg64(odst + 16384 + 512 + 8, op[1], op[3]);
        stg128(odst + 24576, op[4], op[6], op[8], op[10]);
        stg128(odst + 24576 + 512, op[5], op[7], op[9], op[11]);
        stg128(odst + 32768, op[12], op[14], op[16], op[18]);
        stg128(odst + 32768 + 512, op[13], op[15], op[17], op[19]);
    }
}

__device__ __forceinline__ void swiglu_group(const Ctx& c, const float (&acc)[64], int G, const float2 cg, const float2 cu, uint32_t& lo, uint32_t& hi) {
    float h[4];
#pragma unroll
    for (int e = 0; e < 4; e++) {
        const float m = (e < 2) ? c.m0 : c.m1, ga = (e < 2) ? c.ga0 : c.ga1, gb = (e < 2) ? c.gb0 : c.gb1;
        const float gate = fmaf(m, (e & 1) ? cg.y : cg.x, acc[4 * G + e]), up = fmaf(m, (e & 1) ? cu.y : cu.x, acc[32 + 4 * G + e]);
        h[e] = (gate * up) * fmaf(tanh_fast(gate * ga), gb, gb);
    }
    lo = pack2(h[0], h[1]);
    hi = pack2(h[2], h[3]);
}
template <int F, int G0, int G1>
__device__ __forceinline__ void swiglu_pre(const Ctx& c, float2 (&cs)[8]) {
#pragma unroll
    for (int G = G0; G < G1; G++) {
        cs[2 * (G - G0)] = lds64(c.sb + sm_csb(F) + (8 * G + 2 * c.q) * 4);
        cs[2 * (G - G0) + 1] = lds64(c.sb + sm_csb(F) + 256 + (8 * G + 2 * c.q) * 4);
    }
}
template <int F, int G0, int G1, int NPRE>
__device__ __forceinline__ void swiglu_groups(const Ctx& c, const float (&acc)[64], const float2 (&cs)[8], uint32_t (&hp)[8], uint8_t* hdst,
                                              uint32_t sdst = 0) {
#pragma unroll
    for (int G = G0; G < G1; G++) {
        const float2 cg = (G - G0 < NPRE) ? cs[2 * (G - G0)] : lds64(c.sb + sm_csb(F) + (8 * G + 2 * c.q) * 4);
        const float2 cu = (G - G0 < NPRE) ? cs[2 * (G - G0) + 1] : lds64(c.sb + sm_csb(F) + 256 + (8 * G + 2 * c.q) * 4);
        swiglu_group(c, acc, G, cg, cu, hp[G & 3], hp[4 + (G & 3)]);
        if ((G & 3) == 3) {
            if (F >= 1) {
                sts128(sdst + (G >> 2) * 8192, make_uint4(hp[0], hp[1], hp[2], hp[3]));
                sts128(sdst + (G >> 2) * 8192 + 512, make_uint4(hp[4], hp[5], hp[6], hp[7]));
            } else {
                stg128(hdst + (G >> 2) * 8192, hp[0], hp[1], hp[2], hp[3]);
                stg128(hdst + (G >> 2) * 8192 + 512, hp[4], hp[5], hp[6], hp[7]);
            }
        }
    }
}
template <int F>
__device__ __forceinline__ uint32_t own_piece(const Ctx& c) { return c.sb + (F == 1 ? SM_X : SM_OWN) + c.aoff; }
template <int F>
__device__ __forceinline__ void own_done(const Ctx& c) {
    asm volatile("fence.proxy.async.shared::cta;" ::: "memory");
    arrive_local(c, B_WDONE + 1 + F);
}

template <int N>
__device__ __forceinline__ void f_issue(const Ctx& c, float (&acc)[64]) {
    constexpr int S = (N - 20) % 10, SLOT = N & 3;
    mbar_wait(c.bar + (B_RFULL + SLOT) * 8, (N >> 2) & 1);
    wg_fence();
#pragma unroll
    for (int kk = 0; kk < 4; kk++)
        wgmma_n128(acc, c.a_lo + S * 1024 + kk * 2, HI_128, c.b_lo + lbo(8192) + SLOT * 1024 + kk * 128, HI_128, (S | kk) != 0);
    wg_commit();
    wg_wait<1>();
    if (N - 1 <= 45) arrive_both(c, B_REMPTY + ((N - 1) & 3));
    if (N == 43) { mbar_wait(c.bar + B_INIT * 8, 0); arrive_both(c, B_GEMPTY + 0); }
    if (N == 45) arrive_both(c, B_GEMPTY + 1);
    if (N == 48) arrive_both(c, B_GEMPTY + 2);
}

__device__ __forceinline__ void block_edge(const Ctx& c) { mbar_wait(c.bar + B_CS * 8, 0); }

template <bool RF>
__device__ __forceinline__ void q_epilogue(const Ctx& c, float2 (&cs)[8], const float (&q1)[96], const float (&q2)[24], uint32_t (&qp)[20],
                                           uint32_t (&kp)[20], uint32_t (&vp)[20], float (&accA)[64], bool hst, uint8_t* hq_st) {
    qkv_pre<RF, 0, 4>(c, cs);   f_issue<23>(c, accA); qkv_pack<RF, 0, 4>(c, cs, q1, q2, qp, kp, vp);
    qkv_pre<RF, 4, 8>(c, cs);   f_issue<24>(c, accA); qkv_pack<RF, 4, 8>(c, cs, q1, q2, qp, kp, vp);
    if (hst) stg128(hq_st, kp[1], kp[3], kp[7], kp[9]);
    qkv_pre<RF, 8, 12>(c, cs);  f_issue<25>(c, accA); qkv_pack<RF, 8, 12>(c, cs, q1, q2, qp, kp, vp);
    if (hst) { stg128(hq_st + 512, kp[11], kp[13], kp[17], kp[19]); stg128(hq_st + 1024, kp[5], kp[15], vp[1], vp[3]); }
    qkv_pre<RF, 12, 16>(c, cs); f_issue<26>(c, accA); qkv_pack<RF, 12, 16>(c, cs, q1, q2, qp, kp, vp);
    if (hst) stg128(hq_st + 1536, vp[5], vp[7], vp[9], vp[11]);
    qkv_pre<RF, 16, 20>(c, cs); f_issue<27>(c, accA); qkv_pack<RF, 16, 20>(c, cs, q1, q2, qp, kp, vp);
    if (hst) stg128(hq_st + 2048, vp[13], vp[15], vp[17], vp[19]);
    __syncwarp();
    if (c.lane == 0) {
        mbar_arrive(c.bar + (B_HALOR + c.par) * 8);
        if (c.w == 3) mbar_arrive(c.bar + B_HALOW * 8);
    }
    qkv_pre<RF, 20, 25>(c, cs); f_issue<28>(c, accA); qkv_pack<RF, 20, 25>(c, cs, q1, q2, qp, kp, vp);
    transpose_frags<0, 10>(vp);
    qkv_pre<RF, 25, 30>(c, cs); arrive_local(c, B_CSFREE); f_issue<29>(c, accA); qkv_pack<RF, 25, 30>(c, cs, q1, q2, qp, kp, vp);
    transpose_frags<10, 20>(vp);
}

struct AccG {
    float v[80];
    __device__ __forceinline__ float operator[](int i) const { return v[i]; }
};
__device__ __forceinline__ void g_issue(const Ctx& c, AccG& acc, int slot, int parity, bool first, int t, bool own = false) {
    if (own) mbar_wait(c.bar + (B_WDONE + 3) * 8, 0);
    if (!first) mbar_wait(c.bar + (B_GFULL + slot) * 8, parity);
    wg_fence();
    const uint32_t s0 = (c.sb & 0x3FFFF) >> 4, st = s0 + slot * (G_STAGE >> 4);
    const uint32_t alo = (own ? s0 + (SM_OWN >> 4) : st) + c.par * 256 + lbo(16), blo = st + 1024 + lbo(4096);
#pragma unroll
    for (int kk = 0; kk < 4; kk++) {
        wgmma_n160(acc.v, alo + (kk >> 1) * 512 + (kk & 1) * 2, HI_64, blo + (kk >> 1) * 768 + (kk & 1) * 128, HI_128, !(first && kk == 0));
    }
    wg_commit();
}

template <int N, int BIT, int M>
__device__ __forceinline__ void halve(float (&acc)[M], int lane) {
    const bool up = lane & BIT;
#pragma unroll
    for (int e = 0; e < N; e++) {
        const float lo = acc[e], hi = acc[e + N];
        const float send = up ? lo : hi, keep = up ? hi : lo;
        acc[e] = keep + __shfl_xor_sync(0xffffffffu, send, BIT);
    }
}
template <int O, int M>
__device__ __forceinline__ void acc8(float (&acc)[M], const uint4& v) {
    acc[O + 0] += bf_lo(v.x); acc[O + 1] += bf_hi(v.x); acc[O + 2] += bf_lo(v.y); acc[O + 3] += bf_hi(v.y);
    acc[O + 4] += bf_lo(v.z); acc[O + 5] += bf_hi(v.z); acc[O + 6] += bf_lo(v.w); acc[O + 7] += bf_hi(v.w);
}
__device__ __forceinline__ uint4 ldg_nc(const void* p) {
    uint4 v; asm volatile("ld.global.nc.v4.u32 {%0,%1,%2,%3}, [%4];" : "=r"(v.x), "=r"(v.y), "=r"(v.z), "=r"(v.w) : "l"(p)); return v;
}

constexpr uint32_t H_BUF = 32768, H_RED = 6 * H_BUF;
constexpr int H_FULL = 0, H_EMPTY = 6;
__device__ __forceinline__ uint4 f4_bits(float a, float b, float c, float d) {
    return make_uint4(__float_as_uint(a), __float_as_uint(b), __float_as_uint(c), __float_as_uint(d));
}
__device__ __forceinline__ void helper_cta(int h, uint32_t sb, const Maps& maps, const __nv_bfloat16* wqkv,
                                           const __nv_bfloat16* wo, const __nv_bfloat16* w2) {
    const int t = threadIdx.x, warp = __shfl_sync(0xffffffffu, t >> 5, 0), lane = t & 31;
    const uint32_t bar = sb + SM_BAR;
    if (t == 0) {
        for (int i = 0; i < 6; i++) { mbar_init(bar + (H_FULL + i) * 8, 1); mbar_init(bar + (H_EMPTY + i) * 8, 8); }
        asm volatile("fence.mbarrier_init.release.cluster;" ::: "memory");
    }
    __syncthreads();
    if (warp == 11) {
        const CUtensorMap* mc = (h >> 1) ? &maps.w3c : &maps.w1c;
        int s = 0, ph = 1;
#pragma unroll 1
        for (int i = 0; i < 50; i++) {
            mbar_wait(bar + (H_EMPTY + s) * 8, ph);
            if (elect_one()) {
                if (i < 20) {
                    mbar_expect_tx(bar + (H_FULL + s) * 8, 32768);
                    tma2(sb + s * H_BUF, &maps.wqc, 512 * h + 256 * (i & 1), 64 * (9 - (i >> 1)), bar + (H_FULL + s) * 8);
                } else {
                    const int f = (i - 20) / 10, r = (i - 20) % 10;
                    mbar_expect_tx(bar + (H_FULL + s) * 8, 32768);
                    tma2(sb + s * H_BUF, mc, 512 * f + 256 * (r & 1), 320 * (h & 1) + 64 * (r >> 1), bar + (H_FULL + s) * 8);
                }
            }
            if (++s == 6) { s = 0; ph ^= 1; }
        }
        return;
    }
    if (warp >= 8) return;
    const unsigned tag = ld_relaxed(&g_cntO[0]) / 8 + 1;
    int s = 0, ph = 0;
#pragma unroll 1
    for (int job = 0; job < 4; job++) {
        float acc[2][8];
#pragma unroll
        for (int e = 0; e < 8; e++) acc[0][e] = acc[1][e] = 0.f;
#pragma unroll 1
        for (int rb = 0; rb < (job ? 5 : 10); rb++) {
#pragma unroll
            for (int ch = 0; ch < 2; ch++) {
                mbar_wait(bar + (H_FULL + s) * 8, ph);
                uint4 v[8];
#pragma unroll
                for (int r = 0; r < 8; r++) v[r] = lds128(sb + s * H_BUF + (warp * 8 + r) * 512 + lane * 16);
#pragma unroll
                for (int r = 0; r < 8; r++) acc8<0>(acc[ch], v[r]);
                __syncwarp();
                if (lane == 0) mbar_arrive(bar + (H_EMPTY + s) * 8);
                if (++s == 6) { s = 0; ph ^= 1; }
            }
        }
#pragma unroll
        for (int ch = 0; ch < 2; ch++) {
            sts128(sb + H_RED + (warp * 512 + ch * 256 + lane * 8) * 4, f4_bits(acc[ch][0], acc[ch][1], acc[ch][2], acc[ch][3]));
            sts128(sb + H_RED + (warp * 512 + ch * 256 + lane * 8 + 4) * 4, f4_bits(acc[ch][4], acc[ch][5], acc[ch][6], acc[ch][7]));
        }
        bar_sync<1, 256>();
        {
            float s0 = 0.f, s1 = 0.f;
#pragma unroll
            for (int r = 0; r < 8; r++) { const float2 v = lds64(sb + H_RED + (r * 512 + 2 * t) * 4); s0 += v.x; s1 += v.y; }
            if (job == 0) { if (512 * h + 2 * t < 1920) st_tag2(&g_csA[512 * h + 2 * t], tagged(tag, s0), tagged(tag, s1)); }
            else st_tag2(&g_csB[((h & 1) * 2 + (h >> 1)) * kF + 512 * (job - 1) + 2 * t], tagged(tag, s0), tagged(tag, s1));
        }
        bar_sync<1, 256>();
    }
#pragma unroll 1
    for (int k = h * 256 + t; k < 6400 + 15360; k += 4 * 256) {
        const __nv_bfloat16* p = (k < 6400) ? wo + (size_t)k * 64 : w2 + (size_t)(k - 6400) * 64;
        asm volatile("prefetch.global.L2 [%0];" ::"l"(p));
    }
}

}

__global__ void __cluster_dims__(2, 1, 1) __launch_bounds__(384, 1)
fused_block_kernel(const __grid_constant__ Maps maps, const __nv_bfloat16* __restrict__ x, const __nv_bfloat16* __restrict__ wqkv,
                   const __nv_bfloat16* __restrict__ w1, const __nv_bfloat16* __restrict__ w3,
                   const __nv_bfloat16* __restrict__ wo, const __nv_bfloat16* __restrict__ w2, __nv_bfloat16* __restrict__ out) {
    extern __shared__ __align__(1024) uint8_t smem_raw[];
    const uint32_t sb = smem_u32(smem_raw);
    const int warp = __shfl_sync(0xffffffffu, threadIdx.x >> 5, 0);
    const int lane = threadIdx.x & 31;
    uint32_t rank;
    asm("mov.u32 %0, %%cluster_ctarank;" : "=r"(rank));
    const int b = blockIdx.x;
    if (b >= 128) {
        helper_cta(b - 128, sb, maps, wqkv, wo, w2);
        return;
    }
    const int pair = b >> 1;
    const int kq = (pair >> 3) & 3;
    const int slot = 4 * (kq >> 1) + ((pair & 1) ? 1 + (kq & 1) : 3 * (kq & 1));
    const int tile = (2 * ((pair & 7) >> 1) + (pair >> 5)) * 2 + rank;
    const int jj = slot >> 1;
    const int half = (slot ^ (slot >> 1)) & 1;
    const int own_i = 2 * (slot >> 2) + ((slot & 3) >> 1);
    auto hslot = [&](int i) { return 4 * ((i >> 1) & 1) + (half ? 1 + (i & 1) : 3 * (i & 1)); };
    const bool rf = (slot & 3) == 3;
    const int wcol = 80 * slot + (rf ? 16 : 0), wcolr = 80 * slot + (rf ? 0 : 64);

    uint4 xv[X_LSU ? 4 * X_LSU : 1];
    if (X_LSU && warp < 8) {
#pragma unroll
        for (int i = 0; i < 4 * X_LSU; i++) {
            const int p = threadIdx.x + 256 * (i & 3), r = p >> 3;
            xv[i] = ldg_nc(x + (size_t)(tile * 128 + 2 * (r & 63) + (r >> 6)) * kD + (i >> 2) * 64 + (p & 7) * 8);
        }
    }
    if (warp == 8) {
        if (elect_one()) {
#pragma unroll
            for (int i = B_RFULL; i < B_GFULL; i++) mbar_init(sb + SM_BAR + i * 8, bar_count(i));
#pragma unroll
            for (int i = 0; i < 3; i++) mbar_init(sb + SM_BAR + (B_XFULL + i) * 8, bar_count(B_XFULL + i));
            asm volatile("fence.mbarrier_init.release.cluster;" ::: "memory");
        }
        __syncwarp();
    }
    asm volatile("barrier.cluster.arrive.relaxed.aligned;" ::: "memory");
    if (warp == 8) {
        if (X_LSU == 0 && elect_one()) {
            mbar_expect_tx(sb + SM_BAR + B_XFULL * 8, 16384);
            tma3(sb + SM_X, &maps.x, 0, tile * 64, 0, sb + SM_BAR + B_XFULL * 8);
        }
        __syncwarp();
    } else if (warp == 9) {
        if (elect_one()) {
#pragma unroll
            for (int i = B_XFULL + 3; i < B_RFULL; i++) mbar_init(sb + SM_BAR + i * 8, bar_count(i));
#pragma unroll
            for (int i = B_GFULL; i < B_GFULL + 7; i++) mbar_init(sb + SM_BAR + i * 8, bar_count(i));
            asm volatile("fence.mbarrier_init.release.cluster;" ::: "memory");
        }
        __syncwarp();
    } else if (warp == 10) {
        if (elect_one()) {
#pragma unroll
            for (int i = B_GFULL + 7; i < B_WDONE + 1; i++) mbar_init(sb + SM_BAR + i * 8, bar_count(i));
            asm volatile("fence.mbarrier_init.release.cluster;" ::: "memory");
        }
        __syncwarp();
    } else if (warp == 11) {
        if (elect_one()) {
#pragma unroll
            for (int i = B_WDONE + 1; i < B_COUNT; i++) mbar_init(sb + SM_BAR + i * 8, bar_count(i));
            asm volatile("fence.mbarrier_init.release.cluster;" ::: "memory");
        }
        __syncwarp();
    }
    asm volatile("barrier.cluster.wait.aligned;" ::: "memory");
    if (warp == 8) {
        if (elect_one()) {
#pragma unroll
            for (int n = 0; n < 4; n++) {
                const uint32_t fb = sb + SM_BAR + (B_RFULL + n) * 8;
                mbar_expect_tx(fb, 15360);
                tma3_mc(sb + SM_RING + n * 16384 + rank * 6144, &maps.wq, wcol, 32 * n + 16 * rank, 0, fb);
                tma3_mc(sb + SM_RING + n * 16384 + 12288 + rank * 1536, &maps.wqr, wcolr, 32 * n + 16 * rank, 0, fb);
                if ((n & 1) && (n + 1) / 2 >= X_LSU) {
                    const int c = (n + 1) / 2;
                    mbar_expect_tx(sb + SM_BAR + (B_XFULL + c) * 8, 16384);
                    tma3(sb + SM_X + c * 16384, &maps.x, c * 64, tile * 64, 0, sb + SM_BAR + (B_XFULL + c) * 8);
                }
            }
        }
        __syncwarp();
    }
    if (X_LSU && warp < 8) {
#pragma unroll
        for (int i = 0; i < 4 * X_LSU; i++) {
            const int p = threadIdx.x + 256 * (i & 3), r = p >> 3;
            sts128(sb + SM_X + (i >> 2) * 16384 + r * 128 + (((p & 7) ^ (r & 7)) << 4), xv[i]);
        }
        asm volatile("fence.proxy.async.shared::cta;" ::: "memory");
        __syncwarp();
        if (lane == 0) {
#pragma unroll
            for (int i = 0; i < X_LSU; i++) mbar_arrive(sb + SM_BAR + (B_XFULL + i) * 8);
        }
    }
    __syncthreads();

    if (warp >= 8) {
        asm volatile("setmaxnreg.dec.sync.aligned.u32 56;");
        const uint32_t bar = launder(sb + SM_BAR);
        const int n0 = half ? 8 - NH0 : NH0;
        auto g_load = [&](int t, int s, int ph, int part) {
            const int u = t - 1 - n0;
            const int kc = (t == 0) ? 18 + slot : (u < 0) ? 10 + NH0 * half + t - 1 : (u < 5) ? 5 * half + u
                         : (u < 8) ? 18 + hslot(own_i + u - 4) : 26 + hslot(own_i + u - 8);
            const int flag = (t == 1) ? 0 : (u == 0) ? 1 : (u >= 5 && u < 8) ? u - 3 : (u >= 9) ? u - 4 : -1;
            const bool own = (t == 0) || (u == 8);
            const uint32_t st = sb + s * G_STAGE, fb = bar + (B_GFULL + s) * 8;
            if (part & 1) {
                mbar_wait(bar + (B_GEMPTY + s) * 8, ph);
                if (elect_one()) {
                    const bool isO = kc < 10;
                    const int a0 = ((isO ? kc : kc - 10) * 2 + rank) * 4;
                    mbar_expect_tx(fb, own ? 20480 : 16384 + 20480);
                    tma5_mc(st + 16384 + rank * 12288, isO ? &maps.wo2 : &maps.w22, 160 * jj + 32 * (jj & 1), a0, fb);
                    tma4_mc(st + 16384 + rank * 12288 + 8192, isO ? &maps.wo1 : &maps.w21, 160 * jj + ((jj & 1) ? 0 : 128), a0, fb);
                }
            }
            if ((part & 2) && !own) {
                if (flag >= 0) mbar_wait(bar + (B_FLAG + flag) * 8, 0);
                if (t == 5) mbar_wait(bar + B_H1OUT * 8, 0);
                if (elect_one()) bulk_g2s(st, g_act + (size_t)(tile * 34 + kc) * 16384, 16384, fb);
            }
        };
        if (warp == 8) {
            const uint32_t ring = launder(sb + SM_RING);
#pragma unroll 1
            for (int n = 4; n < 20; n++) {
                const int s = n & 3;
                mbar_wait(bar + (B_REMPTY + s) * 8, ((n >> 2) - 1) & 1);
                const int c = (n <= 16 && !(n & 1)) ? n / 2 + 1 : 0;
                if (elect_one()) {
                    mbar_expect_tx(bar + (B_RFULL + s) * 8, 15360);
                    tma3_mc(ring + s * 16384 + rank * 6144, &maps.wq, wcol, 32 * n + 16 * rank, 0, bar + (B_RFULL + s) * 8);
                    tma3_mc(ring + s * 16384 + 12288 + rank * 1536, &maps.wqr, wcolr, 32 * n + 16 * rank, 0, bar + (B_RFULL + s) * 8);
                    if (c > 0) {
                        mbar_expect_tx(bar + (B_XFULL + c) * 8, 16384);
                        tma3(sb + SM_X + c * 16384, &maps.x, c * 64, tile * 64, 0, bar + (B_XFULL + c) * 8);
                    }
                }
            }
            const CUtensorMap* mf = rank ? &maps.w3 : &maps.w1;
            {
                int col = 64 * slot, k = 0;
#pragma unroll 1
                for (int n = 20; n < 50; n++) {
                    const int s = n & 3;
                    mbar_wait(bar + (B_REMPTY + s) * 8, ((n >> 2) - 1) & 1);
                    if (elect_one()) {
                        mbar_expect_tx(bar + (B_RFULL + s) * 8, 16384);
                        tma2_mc(ring + s * 16384 + rank * 8192, mf, col, k, bar + (B_RFULL + s) * 8);
                    }
                    k += 64;
                    if (k == 640) { k = 0; col += 512; }
                }
            }
            constexpr int T1 = 2;
            int s = T1, ph = 0;
            const int nt = 13 + n0;
#pragma unroll 1
            for (int t = T1; t < nt; t++) {
                g_load(t, s, ph, 3);
                if (++s == 5) { s = 0; ph ^= 1; }
            }
        } else {
            const int a = warp - 9;
            const unsigned tag = ld_relaxed(&g_cntO[tile * 32]) / 8 + 1;
            if (a == 0) {
                mbar_wait(bar + (B_XFULL + CS_WAIT) * 8, 0);
                {
                    const int n0 = 4 * lane, n1 = 128 + 4 * (lane < 28 ? lane : 27);
                    const unsigned* p0 = &g_csA[(n0 >> 6) * kD + wcol + (n0 & 63)];
                    const unsigned* p1 = &g_csA[(n1 < 192) ? 2 * kD + wcol + (n1 & 63) : ((n1 - 192) >> 4) * kD + wcolr + ((n1 - 192) & 15)];
                    uint4 v0, v1;
                    gather2(p0, p1, tag, v0, v1);
                    sts128(sb + SM_CS + lane * 16, f4_bits(tag_val(v0.x), tag_val(v0.y), tag_val(v0.z), tag_val(v0.w)));
                    if (lane < 28) sts128(sb + SM_CS + 512 + lane * 16, f4_bits(tag_val(v1.x), tag_val(v1.y), tag_val(v1.z), tag_val(v1.w)));
                    __syncwarp();
                    if (lane == 0) mbar_arrive(bar + B_CS * 8);
                }
                mbar_wait(bar + B_HALOW * 8, 0);
                if (lane == 0) {
                    if (tile < 15) { fence_gpu(); st_relaxed(&g_flagHalo[(tile * 8 + slot) * 32], tag); }
                    if (tile > 0) poll_ge(&g_flagHalo[((tile - 1) * 8 + slot) * 32], tag);
                    mbar_arrive(bar + B_HALOR * 8);
                    mbar_arrive(bar + (B_HALOR + 1) * 8);
                }
                __syncwarp();
                poll_multi(&g_cntH[tile * 32], tag * 8, bar + (B_FLAG + 0) * 8, lane == 0);
                const unsigned* fl = &g_flagH[(tile * 8 + hslot(own_i + lane + 1)) * 32];
                poll_multi(lane < 3 ? fl : &g_cntO[tile * 32], lane < 3 ? tag : tag * 8, bar + (lane < 3 ? B_FLAG + 2 + lane : B_FLAG + 1) * 8, lane < 4);
                poll_multi(fl + 16 * 8 * 32, tag, bar + (B_FLAG + 5 + (lane & 3)) * 8, lane < 3);
            } else {
                {
                    const int t = 16 * slot + 8 * (a - 1) + (lane >> 2);
                    const uint32_t rowa = sb + SM_X + ((t & 1) * 64 + (t >> 1)) * 128 + (lane & 3) * 32;
                    float x0 = 0.f, s4[4] = {0.f, 0.f, 0.f, 0.f}, q4[4] = {0.f, 0.f, 0.f, 0.f};
#pragma unroll 1
                    for (int c = 0; c < 10; c++) {
                        mbar_wait(bar + (B_XFULL + c) * 8, 0);
                        const uint4 v0 = lds128(rowa + c * 16384), v1 = lds128(rowa + c * 16384 + 16);
                        if (c == 0) x0 = __shfl_sync(0xffffffffu, bf_lo(v0.x), lane & 28);
                        const uint32_t wv[8] = {v0.x, v0.y, v0.z, v0.w, v1.x, v1.y, v1.z, v1.w};
#pragma unroll
                        for (int e = 0; e < 8; e++) {
                            const float d0 = bf_lo(wv[e]) - x0, d1 = bf_hi(wv[e]) - x0;
                            s4[e & 3] += d0; q4[e & 3] = fmaf(d0, d0, q4[e & 3]);
                            s4[e & 3] += d1; q4[e & 3] = fmaf(d1, d1, q4[e & 3]);
                        }
                    }
                    float ss = (q4[0] + q4[1]) + (q4[2] + q4[3]), sm = (s4[0] + s4[1]) + (s4[2] + s4[3]);
#pragma unroll
                    for (int o = 1; o < 4; o <<= 1) { sm += __shfl_xor_sync(0xffffffffu, sm, o); ss += __shfl_xor_sync(0xffffffffu, ss, o); }
                    if ((lane & 3) == 0) {
                        const float dm = sm * (1.f / kD), var = fmaxf(ss * (1.f / kD) - dm * dm, 0.f);
                        st_tag2(&g_stats[(tile * 128 + t) * 2], tagged(tag, rsqrtf(var + 1e-5f)), tagged(tag, x0 + dm));
                    }
                }
                if (a == 2) {
                    uint4 v0, v1;
                    gather2(&g_stats[(tile * 128 + 2 * lane) * 2], &g_stats[(tile * 128 + 64 + 2 * lane) * 2], tag, v0, v1);
                    asm volatile("st.shared.v2.f32 [%0], {%1,%2};" ::"r"(sb + SM_ST + lane * 8), "f"(tag_val(v0.x)), "f"(-tag_val(v0.y)) : "memory");
                    asm volatile("st.shared.v2.f32 [%0], {%1,%2};" ::"r"(sb + SM_ST + (64 + lane) * 8), "f"(tag_val(v0.z)), "f"(-tag_val(v0.w)) : "memory");
                    asm volatile("st.shared.v2.f32 [%0], {%1,%2};" ::"r"(sb + SM_ST + (32 + lane) * 8), "f"(tag_val(v1.x)), "f"(-tag_val(v1.y)) : "memory");
                    asm volatile("st.shared.v2.f32 [%0], {%1,%2};" ::"r"(sb + SM_ST + (96 + lane) * 8), "f"(tag_val(v1.z)), "f"(-tag_val(v1.w)) : "memory");
                    __syncwarp();
                    if (lane == 0) mbar_arrive(bar + B_ST * 8);
#pragma unroll 1
                    for (int r = 0; r < 2; r++) {
                        mbar_wait(bar + (B_WDONE + r) * 8, 0);
                        if (lane == 0) { fence_gpu(); red_add(r ? &g_cntO[tile * 32] : &g_cntH[tile * 32], 1); }
                        __syncwarp();
                    }
#pragma unroll 1
                    for (int r = 2; r < 4; r++) {
                        mbar_wait(bar + (B_WDONE + r) * 8, 0);
                        if (elect_one()) {
                            asm volatile("cp.async.bulk.global.shared::cta.bulk_group [%0], [%1], %2;"
                                         ::"l"(g_act + (size_t)(tile * 34 + 2 + 8 * r + slot) * 16384), "r"(sb + (r == 2 ? SM_X : SM_OWN)), "r"(16384) : "memory");
                            asm volatile("cp.async.bulk.commit_group;" ::: "memory");
                            asm volatile("cp.async.bulk.wait_group 0;" ::: "memory");
                            st_relaxed(&g_flagH[((r - 2) * 128 + tile * 8 + slot) * 32], tag);
                            if (r == 2) mbar_arrive(bar + B_H1OUT * 8);
                        }
                        __syncwarp();
                    }
                } else {
#pragma unroll 1
                    for (int f = 0; f < 3; f++) {
                        uint4 v, w;
                        int it = 0;
#pragma unroll 1
                        while (true) {
                            v = ld_tag4(&g_csB[(lane >> 4) * kF + 512 * f + 64 * slot + 4 * (lane & 15)]);
                            w = ld_tag4(&g_csB[(2 + (lane >> 4)) * kF + 512 * f + 64 * slot + 4 * (lane & 15)]);
                            if (__all_sync(0xffffffffu, tag_ok(v, tag) && tag_ok(w, tag)) || ++it > (1 << 15)) break;
                        }
                        if (f == 1) mbar_wait(bar + B_CSFREE * 8, 0);
                        sts128(sb + (f == 0 ? SM_CSB0 : SM_CS + (f - 1) * 512) + lane * 16,
                               f4_bits(tag_val(v.x) + tag_val(w.x), tag_val(v.y) + tag_val(w.y), tag_val(v.z) + tag_val(w.z), tag_val(v.w) + tag_val(w.w)));
                        __syncwarp();
                        if (lane == 0) mbar_arrive(bar + (B_CSB + f) * 8);
                        if (f == 0) {
#pragma unroll 1
                            for (int i = 0; i < 10; i++) {
                                const int p = slot * 10 + i, xc = p >> 3, pi = p & 7;
                                if (elect_one()) tma3_store(&maps.o64, sb + SM_X + xc * 16384 + pi * 2048, 64 * xc, tile * 64 + 16 * (pi & 3), pi >> 2);
                                const long long t0 = clock64();
                                while (clock64() - t0 < INIT_GAP) { }
                            }
                            if (elect_one()) {
                                asm volatile("cp.async.bulk.commit_group;" ::: "memory");
                                asm volatile("cp.async.bulk.wait_group 0;" ::: "memory");
                                asm volatile("fence.proxy.async;" ::: "memory");
                                mbar_arrive(bar + (B_WDONE + 1) * 8);
                                mbar_arrive(bar + B_INIT * 8);
                            }
                        }
                    }
#pragma unroll 1
                    for (int i = 0; i < 4; i++) {
                        g_load(i >> 1, i >> 1, 0, 1 + (i & 1));
                        spin(G_AUX_GAP);
                    }
                }
            }
        }
    } else {
        asm volatile("setmaxnreg.inc.sync.aligned.u32 224;");
        Ctx c;
        c.sb = sb;
        c.bar = sb + SM_BAR;
        c.lane = lane; c.q = lane & 3; c.g = lane >> 2; c.w = warp & 3; c.par = warp >> 2;
        c.rbar = mapa(c.bar, lane & 1);
        c.a_lo = ((sb & 0x3FFFF) >> 4) + c.par * 512 + lbo(16);
        c.b_lo = ((sb + SM_RING) & 0x3FFFF) >> 4;
        const int idx0 = c.w * 16 + c.g;
        c.aoff = piece_off();

        float q1[96], q2[24];
#pragma unroll
        for (int n = 0; n < 20; n++) {
            if ((n & 1) == 0) mbar_wait(c.bar + (B_XFULL + n / 2) * 8, 0);
            mbar_wait(c.bar + (B_RFULL + (n & 3)) * 8, (n >> 2) & 1);
            wg_fence();
#pragma unroll
            for (int h = 0; h < 2; h++) {
                const uint32_t alo = c.a_lo + (n >> 1) * 1024 + ((n & 1) * 2 + h) * 2;
                wgmma_n192(q1, alo, HI_128, c.b_lo + lbo(2048) + (n & 3) * 1024 + h * 384, HI_128, (n | h) != 0);
                wgmma_n48(q2, alo, HI_128, c.b_lo + lbo(512) + (n & 3) * 1024 + 768 + h * 96, HI_32, (n | h) != 0);
            }
            wg_commit();
            wg_wait<1>();
            if (n > 0) arrive_both(c, B_REMPTY + ((n - 1) & 3));
        }

        float accA[64], accB[64];
        uint32_t qp[20], kp[20], vp[20], hk[10], hv[10], op[20], hp[8];
        const bool first = (tile == 0) && (c.w == 0);
        float2 cs[8];
        f_issue<20>(c, accA);
        f_issue<21>(c, accA);
        f_issue<22>(c, accA);
        {
            mbar_wait(c.bar + B_ST * 8, 0);
            const float2 s0 = lds64(sb + SM_ST + (c.par * 64 + idx0) * 8), s1 = lds64(sb + SM_ST + (c.par * 64 + idx0 + 8) * 8);
            c.r0 = s0.x; c.m0 = s0.y; c.r1 = s1.x; c.m1 = s1.y;
            mbar_wait(c.bar + B_CS * 8, 0);
        }
        const int hdt = (c.w == 3) ? tile + 1 : tile;
        const bool hst = hdt < 16;
        uint8_t* hq_st = (uint8_t*)(g_halo + (size_t)(((hdt * 8 + slot) * 2 + c.par) * 4 + ((c.w + 1) & 3)) * 160 + lane);
        if ((slot & 3) == 3) q_epilogue<true>(c, cs, q1, q2, qp, kp, vp, accA, hst, hq_st);
        else q_epilogue<false>(c, cs, q1, q2, qp, kp, vp, accA, hst, hq_st);
        swiglu_consts(c, c.r0, c.r1);

        uint8_t* hdst = nullptr;
        mbar_wait(c.bar + B_CSB * 8, 0);
        swiglu_pre<0, 0, 2>(c, cs); f_issue<30>(c, accB); swiglu_groups<0, 0, 2, 2>(c, accA, cs, hp, hdst);
        swiglu_pre<0, 2, 3>(c, cs); f_issue<31>(c, accB); swiglu_groups<0, 2, 3, 1>(c, accA, cs, hp, hdst);
        hdst = act_piece(c, tile) + (10 + slot) * 16384;
        swiglu_pre<0, 3, 4>(c, cs); f_issue<32>(c, accB); swiglu_groups<0, 3, 4, 1>(c, accA, cs, hp, hdst);
        swiglu_pre<0, 4, 6>(c, cs); f_issue<33>(c, accB); swiglu_groups<0, 4, 6, 2>(c, accA, cs, hp, hdst);
        swiglu_pre<0, 6, 7>(c, cs); f_issue<34>(c, accB); swiglu_groups<0, 6, 7, 1>(c, accA, cs, hp, hdst);
        uint4 t0, t1, t2, t3, t4;
        {
            mbar_wait(c.bar + (B_HALOR + c.par) * 8, 0);
            const uint4* hq = g_halo + (size_t)(((tile * 8 + slot) * 2 + c.par) * 4 + c.w) * 160 + lane;
            t0 = __ldcg(hq); t1 = __ldcg(hq + 32); t2 = __ldcg(hq + 64); t3 = __ldcg(hq + 96); t4 = __ldcg(hq + 128);
        }
        hdst = act_piece(c, tile) + (10 + slot) * 16384;
        swiglu_pre<0, 7, 8>(c, cs); f_issue<35>(c, accB); swiglu_groups<0, 7, 8, 1>(c, accA, cs, hp, hdst);
        arrive_local(c, B_WDONE + 0);
        hk[0] = t0.x; hk[1] = t0.y; hk[3] = t0.z; hk[4] = t0.w; hk[5] = t1.x; hk[6] = t1.y; hk[8] = t1.z; hk[9] = t1.w;
        hk[2] = t2.x; hk[7] = t2.y; hv[0] = t2.z; hv[1] = t2.w; hv[2] = t3.x; hv[3] = t3.y; hv[4] = t3.z; hv[5] = t3.w;
        hv[6] = t4.x; hv[7] = t4.y; hv[8] = t4.z; hv[9] = t4.w;
        float sc[4][4], mx[4][2];
        uint32_t pr[4][4];
        {
            float lg[4][3][4], nq;
            uint32_t qs[4][2];
            attn_prep(c, first, qp, qs, nq);
            f_issue<36>(c, accB);
            block_edge(c);
            attn_logits<0>(qp, qs, kp, hk, nq, lg[0][0], lg[0][1], lg[0][2]); attn_logits<1>(qp, qs, kp, hk, nq, lg[1][0], lg[1][1], lg[1][2]);
            attn_logits<2>(qp, qs, kp, hk, nq, lg[2][0], lg[2][1], lg[2][2]); attn_logits<3>(qp, qs, kp, hk, nq, lg[3][0], lg[3][1], lg[3][2]);
            f_issue<37>(c, accB); attn_select(c, lg, sc); attn_max(sc, mx);
        }
        f_issue<38>(c, accB); attn_exp(c, sc, mx);
        f_issue<39>(c, accB); attn_sum(mx);

        f_issue<40>(c, accA); attn_probs(c, sc, mx, pr);
        transpose_frags<0, 10>(hv);
        {
            float ov[4][3][4];
            f_issue<41>(c, accA);
            block_edge(c);
            attn_pv<0>(pr[0], vp, hv, ov[0]); attn_pv<1>(pr[1], vp, hv, ov[1]); attn_pv<2>(pr[2], vp, hv, ov[2]); attn_pv<3>(pr[3], vp, hv, ov[3]);
            f_issue<42>(c, accA);
            attn_pack(c, ov, op);
        }
        o_store(c, tile, slot, op);
        f_issue<43>(c, accA);
        arrive_local(c, B_WDONE + 1);
        mbar_wait(c.bar + (B_CSB + 1) * 8, 0);
        {
            const uint32_t sa = launder(sb + SM_ST + (c.par * 64 + idx0) * 8);
            const float2 s0 = lds64(sa), s1 = lds64(sa + 64);
            c.m0 = s0.y; c.m1 = s1.y;
            swiglu_consts(c, s0.x, s1.x);
        }
        swiglu_pre<1, 0, 2>(c, cs); f_issue<44>(c, accA); swiglu_groups<1, 0, 2, 2>(c, accB, cs, hp, nullptr, 0);
        swiglu_pre<1, 2, 4>(c, cs); f_issue<45>(c, accA); swiglu_groups<1, 2, 4, 2>(c, accB, cs, hp, nullptr, own_piece<1>(c));
        swiglu_pre<1, 4, 6>(c, cs); f_issue<46>(c, accA); swiglu_groups<1, 4, 6, 2>(c, accB, cs, hp, nullptr, 0);
        swiglu_pre<1, 6, 7>(c, cs); f_issue<47>(c, accA); swiglu_groups<1, 6, 7, 1>(c, accB, cs, hp, nullptr, 0);
        swiglu_pre<1, 7, 8>(c, cs); f_issue<48>(c, accA); swiglu_groups<1, 7, 8, 1>(c, accB, cs, hp, nullptr, own_piece<1>(c));
        own_done<1>(c);
        f_issue<49>(c, accA);

        AccG accG;
        mbar_wait(c.bar + (B_CSB + 2) * 8, 0);
        float2 cs2[8];
        swiglu_pre<2, 0, 4>(c, cs);
        swiglu_pre<2, 4, 8>(c, cs2);
        mbar_wait(c.bar + (B_GEMPTY + 2) * 8, 0);
        mbar_wait(c.bar + (B_WDONE + 2) * 8, 0);
        mbar_wait(c.bar + (B_GFULL + 0) * 8, 0);
        wg_wait<0>();
        arrive_both(c, B_GEMPTY + 3);
        arrive_both(c, B_GEMPTY + 4);
        {
            const uint32_t sdst = own_piece<2>(c);
            swiglu_groups<2, 0, 4, 4>(c, accA, cs, hp, nullptr, sdst);
            swiglu_groups<2, 4, 8, 4>(c, accA, cs2, hp, nullptr, sdst);
        }
        g_issue(c, accG, 0, 0, true, 0);
        g_issue(c, accG, 1, 0, false, 1);
        own_done<2>(c);
        wg_wait<1>(); arrive_both(c, B_GEMPTY + 0);
        g_issue(c, accG, 2, 0, false, 2); wg_wait<1>(); arrive_both(c, B_GEMPTY + 1);
        g_issue(c, accG, 3, 0, false, 3); wg_wait<1>(); arrive_both(c, B_GEMPTY + 2);
        g_issue(c, accG, 4, 0, false, 4); wg_wait<1>(); arrive_both(c, B_GEMPTY + 3);
        g_issue(c, accG, 0, 1, false, 5); wg_wait<1>(); arrive_both(c, B_GEMPTY + 4);
        int gs = 1, gph = 1;
        const int n0 = half ? 8 - NH0 : NH0, nt = 13 + n0;
#pragma unroll 1
        for (int t = 6; t < nt; t++) {
            g_issue(c, accG, gs, gph, false, t, t == n0 + 9);
            wg_wait<1>();
            if (t + 4 < nt) arrive_both(c, B_GEMPTY + (gs == 0 ? 4 : gs - 1));
            if (++gs == 5) { gs = 0; gph ^= 1; }
        }
        const int R = (lane & 7) + (lane & 8), hi = lane >> 4;
        const int orow = tile * 64 + c.w * 16;
        auto stage_box = [&](int bx, uint32_t dst) {
#pragma unroll
            for (int p = 0; p < 2; p++) {
                const int G = 4 * bx + 2 * p;
                stsm4(dst + R * 64 + ((((G & 3) + hi) ^ ((R >> 1) & 3)) << 4),
                      pack2(accG[4 * G], accG[4 * G + 1]), pack2(accG[4 * G + 2], accG[4 * G + 3]),
                      pack2(accG[4 * G + 4], accG[4 * G + 5]), pack2(accG[4 * G + 6], accG[4 * G + 7]));
            }
        };
        auto out_col = [&](int bx) { return 160 * jj + ((jj & 1) ? (bx < 4 ? 32 * bx + 32 : 0) : 32 * bx); };
        wg_wait<0>();
        {
            if (c.par == 0) bar_sync<1, 128>(); else bar_sync<2, 128>();
            const uint32_t s64 = sb + (c.w >> 1) * 8192 + c.par * 4096 + (c.w & 1) * 2048, s32 = sb + 2 * G_STAGE + c.par * 4096 + c.w * 1024;
            auto stage64 = [&](int bb) {
#pragma unroll
                for (int p = 0; p < 4; p++) {
                    const int G = 8 * bb + 2 * p;
                    stsm4(s64 + bb * G_STAGE + R * 128 + (((2 * p + hi) ^ (R & 7)) << 4),
                          pack2(accG[4 * G], accG[4 * G + 1]), pack2(accG[4 * G + 2], accG[4 * G + 3]),
                          pack2(accG[4 * G + 4], accG[4 * G + 5]), pack2(accG[4 * G + 6], accG[4 * G + 7]));
                }
            };
            stage64(0);
            asm volatile("fence.proxy.async.shared::cta;" ::: "memory");
            __syncwarp();
            if (elect_one()) tma3_red(&maps.o64, s64, out_col(0), orow, c.par);
            stage64(1);
            stage_box(4, s32);
            asm volatile("fence.proxy.async.shared::cta;" ::: "memory");
            __syncwarp();
            if (elect_one()) {
                tma3_red(&maps.o64, s64 + G_STAGE, out_col(2), orow, c.par);
                tma3_red(&maps.o32, s32, out_col(4), orow, c.par);
                asm volatile("cp.async.bulk.commit_group;" ::: "memory");
                asm volatile("cp.async.bulk.wait_group.read 0;" ::: "memory");
            }
        }
        if (c.w == 0) { }
    }
}

namespace {
typedef CUresult (*EncodeFn)(CUtensorMap*, CUtensorMapDataType, cuuint32_t, void*, const cuuint64_t*, const cuuint64_t*, const cuuint32_t*,
                             const cuuint32_t*, CUtensorMapInterleave, CUtensorMapSwizzle, CUtensorMapL2promotion, CUtensorMapFloatOOBfill);

bool encode(EncodeFn fn, CUtensorMap* m, const void* ptr, int rank, const cuuint64_t* dims, const cuuint64_t* strides, const cuuint32_t* box,
            CUtensorMapSwizzle sw) {
    const cuuint32_t es[5] = {1, 1, 1, 1, 1};
    return fn(m, CU_TENSOR_MAP_DATA_TYPE_BFLOAT16, rank, const_cast<void*>(ptr), dims, strides, box, es, CU_TENSOR_MAP_INTERLEAVE_NONE, sw,
              CU_TENSOR_MAP_L2_PROMOTION_L2_128B, CU_TENSOR_MAP_FLOAT_OOB_FILL_NONE) == CUDA_SUCCESS;
}
}

extern "C" void kernel_launch(void* const* d_in, const int* in_sizes, int n_in, void* d_out, int out_size) {
    (void)in_sizes; (void)n_in; (void)out_size;
    const __nv_bfloat16* x = (const __nv_bfloat16*)d_in[0];
    const __nv_bfloat16* wqkv = (const __nv_bfloat16*)d_in[1];
    const __nv_bfloat16* wo = (const __nv_bfloat16*)d_in[2];
    const __nv_bfloat16* w1 = (const __nv_bfloat16*)d_in[4];
    const __nv_bfloat16* w3 = (const __nv_bfloat16*)d_in[5];
    const __nv_bfloat16* w2 = (const __nv_bfloat16*)d_in[6];

    static EncodeFn fn = nullptr;
    if (!fn) {
        void* p = nullptr;
        cudaDriverEntryPointQueryResult st;
        cudaGetDriverEntryPoint("cuTensorMapEncodeTiled", &p, cudaEnableDefault, &st);
        fn = (EncodeFn)p;
        cudaFuncSetAttribute(fused_block_kernel, cudaFuncAttributeMaxDynamicSharedMemorySize, SM_TOTAL);
    }
    Maps maps;
    {
        const cuuint64_t d[3] = {640, 1024, 2}, s[2] = {2560, 1280};
        const cuuint32_t b[3] = {64, 64, 2};
        encode(fn, &maps.x, x, 3, d, s, b, CU_TENSOR_MAP_SWIZZLE_128B);
    }
    {
        const cuuint64_t d[3] = {640, 640, 3}, s[2] = {3840, 1280};
        const cuuint32_t b[3] = {64, 16, 3}, br[3] = {16, 16, 3};
        encode(fn, &maps.wq, wqkv, 3, d, s, b, CU_TENSOR_MAP_SWIZZLE_128B);
        encode(fn, &maps.wqr, wqkv, 3, d, s, br, CU_TENSOR_MAP_SWIZZLE_32B);
    }
    {
        const cuuint64_t d[2] = {1536, 640}, s[1] = {3072};
        const cuuint32_t b[2] = {64, 64};
        encode(fn, &maps.w1, w1, 2, d, s, b, CU_TENSOR_MAP_SWIZZLE_128B);
        encode(fn, &maps.w3, w3, 2, d, s, b, CU_TENSOR_MAP_SWIZZLE_128B);
    }
    {
        const cuuint64_t d[2] = {1920, 640}, s[1] = {3840};
        const cuuint32_t b[2] = {256, 64};
        encode(fn, &maps.wqc, wqkv, 2, d, s, b, CU_TENSOR_MAP_SWIZZLE_NONE);
    }
    {
        const cuuint64_t d[2] = {1536, 640}, s[1] = {3072};
        const cuuint32_t b[2] = {256, 64};
        encode(fn, &maps.w1c, w1, 2, d, s, b, CU_TENSOR_MAP_SWIZZLE_NONE);
        encode(fn, &maps.w3c, w3, 2, d, s, b, CU_TENSOR_MAP_SWIZZLE_NONE);
    }
    {
        const cuuint64_t do5[5] = {640, 2, 80, 4, 2}, d25[5] = {640, 2, 192, 4, 2}, s5[4] = {1280, 10240, 2560, 128};
        const cuuint32_t b5[5] = {64, 2, 4, 4, 2}, b4[4] = {32, 2, 4, 4};
        encode(fn, &maps.wo2, wo, 5, do5, s5, b5, CU_TENSOR_MAP_SWIZZLE_128B);
        encode(fn, &maps.w22, w2, 5, d25, s5, b5, CU_TENSOR_MAP_SWIZZLE_128B);
        encode(fn, &maps.wo1, wo, 4, do5, s5, b4, CU_TENSOR_MAP_SWIZZLE_128B);
        encode(fn, &maps.w21, w2, 4, d25, s5, b4, CU_TENSOR_MAP_SWIZZLE_128B);
    }
    {
        const cuuint64_t d[3] = {640, 1024, 2}, s[2] = {2560, 1280};
        const cuuint32_t b64[3] = {64, 16, 1}, b32[3] = {32, 16, 1};
        encode(fn, &maps.o64, d_out, 3, d, s, b64, CU_TENSOR_MAP_SWIZZLE_128B);
        encode(fn, &maps.o32, d_out, 3, d, s, b32, CU_TENSOR_MAP_SWIZZLE_64B);
    }
    fused_block_kernel<<<132, 384, SM_TOTAL>>>(maps, x, wqkv, w1, w3, wo, w2, (__nv_bfloat16*)d_out);
}
```
